```python
import torch

def _softmax(x, axis=-1):
    return torch.softmax(x, dim=axis)
def _gelu(x):
    return torch.nn.functional.gelu(x, approximate="tanh")
def _silu(x):
    return torch.nn.functional.silu(x)
def _sigmoid(x):
    return torch.sigmoid(x)
def _layernorm(x, axis=-1, eps=1e-5):
    m = x.mean(dim=axis, keepdim=True)
    v = x.var(dim=axis, keepdim=True, unbiased=False)
    return (x - m) / torch.sqrt(v + eps)
def _scatter_add(tgt, idx, src, axis=0):
    return tgt.clone().index_add_(axis, idx, src)
def _segment_sum(src, seg, n):
    out = torch.zeros((n,) + src.shape[1:], dtype=src.dtype)
    return out.index_add_(0, seg, src)
def _pad(x, pw):
    flat = tuple(v for pair in reversed(pw) for v in pair)
    return torch.nn.functional.pad(x, flat)

kernel_name = 'parallel_sum__linear_attn_block__glu_gated_swiglu__prompt'

def setup_inputs():

    _w = (lambda a: (lambda t: t.to(torch.bfloat16) if t.is_floating_point() else t)(torch.as_tensor(a)))
    def _A_setup():
        B, S, D = 1, 2048, 576
        return {
            "x": _w((lambda *s: torch.randn(*s, dtype=torch.bfloat16) * 0.05)(B, S, D)),
            "wqkv": _w((lambda *s: torch.randn(*s, dtype=torch.bfloat16) * 0.05)(D, 3 * D)),
            "wo": _w((lambda *s: torch.randn(*s, dtype=torch.bfloat16) * 0.05)(D, D)),
        }
    _A_in = _A_setup()

    def _B_setup():
        B, S, D, F = 1, 2048, 576, 4608
        return {
            "x": _w((lambda *s: torch.randn(*s, dtype=torch.bfloat16) * 0.05)(B, S, D)),
            "w1": _w((lambda *s: torch.randn(*s, dtype=torch.bfloat16) * 0.2)(D, F) * (2.0 / D) ** 0.5),
            "w3": _w((lambda *s: torch.randn(*s, dtype=torch.bfloat16) * 0.2)(D, F) * (2.0 / D) ** 0.5),
            "w2": _w((lambda *s: torch.randn(*s, dtype=torch.bfloat16) * 0.2)(F, D) * (2.0 / F) ** 0.5),
        }
    _B_in = _B_setup()

    return {
        "A_x": _A_in["x"],
        "A_wqkv": _A_in["wqkv"],
        "A_wo": _A_in["wo"],
        "B_x": _B_in["x"],
        "B_w1": _B_in["w1"],
        "B_w3": _B_in["w3"],
        "B_w2": _B_in["w2"],
    }

def reference(A_x, A_wqkv, A_wo, B_x, B_w1, B_w3, B_w2):
    def _A_ref(x, wqkv, wo):
        B, S, D = x.shape
        H = 32; Dh = D // H
        qkv = (lambda x, *d: x.permute(*d))((x @ wqkv).reshape(B, S, 3, H, Dh), 2, 0, 3, 1, 4)
        q, k, v = qkv[0], qkv[1], qkv[2]
        phi = lambda t: torch.where(t > 0, t + 1, torch.exp(t)) + 1e-6
        pq, pk = phi(q), phi(k)
        kv = torch.einsum("bhsd,bhse->bhde", pk, v)
        z = torch.einsum("bhsd->bhd", pk)
        num = torch.einsum("bhqd,bhde->bhqe", pq, kv)
        den = torch.einsum("bhqd,bhd->bhq", pq, z)[..., None] + 1e-6
        o = num / den
        return (lambda x, *d: x.permute(*d))(o, 0, 2, 1, 3).reshape(B, S, D) @ wo

    def _B_ref(x, w1, w3, w2):
        gate = torch.einsum("bsd,df->bsf", x, w1)
        up = torch.einsum("bsd,df->bsf", x, w3)
        h = _silu(gate) * up
        out = torch.einsum("bsf,fd->bsd", h, w2)
        return out

    x = A_x
    xn = _layernorm(x, axis=-1)
    return x + _A_ref(xn, A_wqkv, A_wo) + _B_ref(xn, B_w1, B_w3, B_w2)
```

```cpp
#include <cuda_runtime.h>
#include <cuda.h>
#include <cuda_bf16.h>
#include <stdint.h>

namespace {

constexpr int S_ = 2048, D_ = 576, F_ = 4608;
constexpr int NTHREADS = 384;

constexpr uint32_t SLOT = 12288;
constexpr uint32_t HB = 6 * SLOT;
constexpr uint32_t HHALF = 73728;
constexpr uint32_t XPITCH = 1168;
constexpr uint32_t PK_T = HB + 36864;
constexpr uint32_t V_T = HB + 55296;
constexpr uint32_t L24_T = HB + HHALF + 46080;
constexpr uint32_t WO_SLOT = HB + 67584;
constexpr uint32_t OT0 = HB, OT1 = HB + 137216;
constexpr uint32_t PS0 = HB + 10240, PS1 = HB + 79872;
constexpr uint32_t KVF = HB + 2 * HHALF;
constexpr uint32_t Q8 = KVF + 6912;
constexpr uint32_t BARS = Q8 + 2048;
constexpr uint32_t SMEM_BYTES = BARS + 512 + 1024;

constexpr uint32_t B_FULL = BARS;
constexpr uint32_t B_EMPTY = BARS + 56;
constexpr uint32_t B_X = BARS + 112;
constexpr uint32_t B_XDONE = BARS + 176;
constexpr uint32_t B_LFULL = BARS + 184;
constexpr uint32_t B_KVT = BARS + 192;
constexpr uint32_t B_KVFREE = BARS + 200;
constexpr uint32_t B_KVRDY = BARS + 208;
constexpr uint32_t B_HFREE = BARS + 216;
constexpr uint32_t B_PUB = BARS + 224;
constexpr uint32_t B_PFULL = BARS + 352;

constexpr uint32_t SPIN_LIMIT = 1u << 22;

__device__ uint4 g_part[16 * 9 * 8 * 2 * 512];
__device__ float4 g_kvp[8 * 16 * 864];
__device__ float4 g_kvs[8 * 864];
__device__ uint32_t g_cnt1[8 * 32], g_cnt2[8 * 32];
__device__ uint32_t g_flag[16 * 9 * 8 * 2];
__device__ uint32_t g_epoch[128];

__device__ __forceinline__ void wg_fence() { asm volatile("wgmma.fence.sync.aligned;\n" ::: "memory"); }
__device__ __forceinline__ void wg_commit() { asm volatile("wgmma.commit_group.sync.aligned;\n" ::: "memory"); }
template <int N> __device__ __forceinline__ void wg_wait() { asm volatile("wgmma.wait_group.sync.aligned %0;\n" ::"n"(N) : "memory"); }
__device__ __forceinline__ uint64_t mkdesc(uint32_t addr, uint32_t lbo, uint32_t sbo, uint32_t sw) {
  return (uint64_t)((addr & 0x3FFFF) >> 4) | ((uint64_t)(lbo >> 4) << 16) | ((uint64_t)(sbo >> 4) << 32) | ((uint64_t)sw << 62);
}
__device__ __forceinline__ void mbar_init(uint32_t a, uint32_t c) { asm volatile("mbarrier.init.shared::cta.b64 [%0], %1;\n" ::"r"(a), "r"(c) : "memory"); }
__device__ __forceinline__ void mbar_expect(uint32_t a, uint32_t b) { asm volatile("mbarrier.arrive.expect_tx.shared::cta.b64 _, [%0], %1;\n" ::"r"(a), "r"(b) : "memory"); }
__device__ __forceinline__ void mbar_arrive(uint32_t a) { asm volatile("mbarrier.arrive.shared::cta.b64 _, [%0];\n" ::"r"(a) : "memory"); }
__device__ __forceinline__ void mbar_wait(uint32_t a, uint32_t ph) {
  asm volatile(
      "{\n.reg .pred p;\n.reg .u32 n;\n"
      "mbarrier.try_wait.parity.shared::cta.b64 p, [%0], %1;\n"
      "@p bra DONE;\n"
      "mov.u32 n, 0;\n"
      "LOOP:\n"
      "mbarrier.try_wait.parity.shared::cta.b64 p, [%0], %1;\n"
      "@p bra DONE;\n"
      "add.u32 n, n, 1;\n"
      "setp.lt.u32 p, n, %2;\n"
      "@p bra LOOP;\n"
      "trap;\n"
      "DONE:\n}\n" ::"r"(a), "r"(ph), "n"(SPIN_LIMIT) : "memory");
}
__device__ __forceinline__ void tma2d(uint32_t dst, const CUtensorMap* m, int c0, int c1, uint32_t bar) {
  asm volatile("cp.async.bulk.tensor.2d.shared::cluster.global.mbarrier::complete_tx::bytes [%0], [%1, {%3, %4}], [%2];\n" ::"r"(dst), "l"(m), "r"(bar), "r"(c0), "r"(c1) : "memory");
}
__device__ __forceinline__ void bulk_g2s(uint32_t dst, const void* src, uint32_t bytes, uint32_t bar) {
  asm volatile("cp.async.bulk.shared::cluster.global.mbarrier::complete_tx::bytes [%0], [%1], %2, [%3];\n" ::"r"(dst), "l"(src), "r"(bytes), "r"(bar) : "memory");
}
__device__ __forceinline__ void prefetch_l2(const void* p) { asm volatile("prefetch.global.L2 [%0];\n" ::"l"(p)); }
__device__ __forceinline__ void fence_async_smem() { asm volatile("fence.proxy.async.shared::cta;\n" ::: "memory"); }
__device__ __forceinline__ void bar_sync(int id, int n) { asm volatile("bar.sync %0, %1;\n" ::"r"(id), "r"(n) : "memory"); }
__device__ __forceinline__ void ldsm4(uint32_t& r0, uint32_t& r1, uint32_t& r2, uint32_t& r3, uint32_t a) {
  asm volatile("ldmatrix.sync.aligned.m8n8.x4.shared.b16 {%0,%1,%2,%3}, [%4];\n" : "=r"(r0), "=r"(r1), "=r"(r2), "=r"(r3) : "r"(a) : "memory");
}
__device__ __forceinline__ void ldsm4t(uint32_t& r0, uint32_t& r1, uint32_t& r2, uint32_t& r3, uint32_t a) {
  asm volatile("ldmatrix.sync.aligned.m8n8.x4.trans.shared.b16 {%0,%1,%2,%3}, [%4];\n" : "=r"(r0), "=r"(r1), "=r"(r2), "=r"(r3) : "r"(a) : "memory");
}
__device__ __forceinline__ void ldsm2t(uint32_t& r0, uint32_t& r1, uint32_t a) {
  asm volatile("ldmatrix.sync.aligned.m8n8.x2.trans.shared.b16 {%0,%1}, [%2];\n" : "=r"(r0), "=r"(r1) : "r"(a) : "memory");
}
__device__ __forceinline__ void stsm4(uint32_t a, uint32_t r0, uint32_t r1, uint32_t r2, uint32_t r3) {
  asm volatile("stmatrix.sync.aligned.m8n8.x4.shared.b16 [%0], {%1,%2,%3,%4};\n" ::"r"(a), "r"(r0), "r"(r1), "r"(r2), "r"(r3) : "memory");
}
__device__ __forceinline__ void sts128(uint32_t a, uint32_t r0, uint32_t r1, uint32_t r2, uint32_t r3) {
  asm volatile("st.shared.v4.b32 [%0], {%1,%2,%3,%4};\n" ::"r"(a), "r"(r0), "r"(r1), "r"(r2), "r"(r3) : "memory");
}
__device__ __forceinline__ void lds128(uint32_t& r0, uint32_t& r1, uint32_t& r2, uint32_t& r3, uint32_t a) {
  asm volatile("ld.shared.v4.b32 {%0,%1,%2,%3}, [%4];\n" : "=r"(r0), "=r"(r1), "=r"(r2), "=r"(r3) : "r"(a) : "memory");
}
__device__ __forceinline__ void sts64(uint32_t a, uint32_t r0, uint32_t r1) { asm volatile("st.shared.v2.b32 [%0], {%1,%2};\n" ::"r"(a), "r"(r0), "r"(r1) : "memory"); }
__device__ __forceinline__ void lds64(uint32_t& r0, uint32_t& r1, uint32_t a) { asm volatile("ld.shared.v2.b32 {%0,%1}, [%2];\n" : "=r"(r0), "=r"(r1) : "r"(a) : "memory"); }
__device__ __forceinline__ void sts32(uint32_t a, uint32_t r0) { asm volatile("st.shared.b32 [%0], %1;\n" ::"r"(a), "r"(r0) : "memory"); }
__device__ __forceinline__ void mma16816(float (&c)[4], uint32_t a0, uint32_t a1, uint32_t a2, uint32_t a3, uint32_t b0, uint32_t b1) {
  asm volatile("mma.sync.aligned.m16n8k16.row.col.f32.bf16.bf16.f32 {%0,%1,%2,%3}, {%4,%5,%6,%7}, {%8,%9}, {%0,%1,%2,%3};\n"
               : "+f"(c[0]), "+f"(c[1]), "+f"(c[2]), "+f"(c[3]) : "r"(a0), "r"(a1), "r"(a2), "r"(a3), "r"(b0), "r"(b1));
}
__device__ __forceinline__ uint32_t pack2(float lo, float hi) {
  uint32_t r;
  asm("cvt.rn.bf16x2.f32 %0, %1, %2;\n" : "=r"(r) : "f"(hi), "f"(lo));
  return r;
}
__device__ __forceinline__ float blo(uint32_t w) { return __uint_as_float(w << 16); }
__device__ __forceinline__ float bhi(uint32_t w) { return __uint_as_float(w & 0xffff0000u); }
__device__ __forceinline__ float rbf(float x) { return __bfloat162float(__float2bfloat16_rn(x)); }
__device__ __forceinline__ float ex2(float x) { float r; asm("ex2.approx.ftz.f32 %0, %1;\n" : "=f"(r) : "f"(x)); return r; }
__device__ __forceinline__ float rcp(float x) { float r; asm("rcp.approx.ftz.f32 %0, %1;\n" : "=f"(r) : "f"(x)); return r; }
__device__ __forceinline__ uint32_t bsub2(uint32_t a, uint32_t b) { uint32_t r; asm("sub.rn.bf16x2 %0, %1, %2;\n" : "=r"(r) : "r"(a), "r"(b)); return r; }
__device__ __forceinline__ uint32_t ld_acq(const uint32_t* p) { uint32_t v; asm volatile("ld.acquire.gpu.global.u32 %0, [%1];\n" : "=r"(v) : "l"(p) : "memory"); return v; }
__device__ __forceinline__ void st_rel(uint32_t* p, uint32_t v) { asm volatile("st.release.gpu.global.u32 [%0], %1;\n" ::"l"(p), "r"(v) : "memory"); }
__device__ __forceinline__ void red_rel(uint32_t* p) { asm volatile("red.release.gpu.global.add.u32 [%0], 1;\n" ::"l"(p) : "memory"); }
__device__ __forceinline__ void wait_ge(const uint32_t* p, uint32_t target) {
  uint32_t n = 0;
  while ((int32_t)(ld_acq(p) - target) < 0) {
    __nanosleep(64);
    if (++n > SPIN_LIMIT) __trap();
  }
}
__device__ __forceinline__ float phi(float t) { return (t > 0.f ? t + 1.f : ex2(t * 1.4426950408889634f)) + 1e-6f; }

#define ACC8(d, o) "+f"(d[o + 0]), "+f"(d[o + 1]), "+f"(d[o + 2]), "+f"(d[o + 3]), "+f"(d[o + 4]), "+f"(d[o + 5]), "+f"(d[o + 6]), "+f"(d[o + 7])
#define REGS32 "{%0,%1,%2,%3,%4,%5,%6,%7,%8,%9,%10,%11,%12,%13,%14,%15,%16,%17,%18,%19,%20,%21,%22,%23,%24,%25,%26,%27,%28,%29,%30,%31}"
__device__ __forceinline__ void wgmma_rs64(float (&d)[32], const uint32_t (&a)[4], uint64_t db, int acc) {
  asm volatile("{\n.reg .pred p;\nsetp.ne.b32 p, %37, 0;\n"
               "wgmma.mma_async.sync.aligned.m64n64k16.f32.bf16.bf16 " REGS32 ", {%32,%33,%34,%35}, %36, p, 1, 1, 1;\n}\n"
               : ACC8(d, 0), ACC8(d, 8), ACC8(d, 16), ACC8(d, 24)
               : "r"(a[0]), "r"(a[1]), "r"(a[2]), "r"(a[3]), "l"(db), "r"(acc));
}
__device__ __forceinline__ void wgmma_ss64(float (&d)[32], uint64_t da, uint64_t db) {
  asm volatile("wgmma.mma_async.sync.aligned.m64n64k16.f32.bf16.bf16 " REGS32 ", %32, %33, 1, 1, 1, 0, 1;\n"
               : ACC8(d, 0), ACC8(d, 8), ACC8(d, 16), ACC8(d, 24)
               : "l"(da), "l"(db));
}
__device__ __forceinline__ void wgmma_rs24(float (&d)[12], const uint32_t (&a)[4], uint64_t db, int acc) {
  asm volatile("{\n.reg .pred p;\nsetp.ne.b32 p, %17, 0;\n"
               "wgmma.mma_async.sync.aligned.m64n24k16.f32.bf16.bf16 {%0,%1,%2,%3,%4,%5,%6,%7,%8,%9,%10,%11}, {%12,%13,%14,%15}, %16, p, 1, 1, 1;\n}\n"
               : ACC8(d, 0), "+f"(d[8]), "+f"(d[9]), "+f"(d[10]), "+f"(d[11])
               : "r"(a[0]), "r"(a[1]), "r"(a[2]), "r"(a[3]), "l"(db), "r"(acc));
}
template <int N> __device__ __forceinline__ void pin(float (&d)[N]) {
#pragma unroll
  for (int i = 0; i < N; i++) asm volatile("" : "+f"(d[i])::"memory");
}

__host__ __device__ constexpr int kv_u0(int i) { return i == 0 ? 0 : i == 1 ? 0 : i == 2 ? 2 : i == 3 ? 4 : 0; }
__host__ __device__ constexpr int kv_nu(int i) { return i == 0 ? 3 : i == 4 ? 9 : 5; }
__host__ __device__ constexpr int kv_base(int i) { return i == 0 ? 0 : i == 1 ? 3 : i == 2 ? 8 : i == 3 ? 13 : 18; }
__host__ __device__ constexpr int o_k0(int t) { return t <= 2 ? 0 : t <= 4 ? 1 : t <= 6 ? 2 : t <= 8 ? 3 : t == 9 ? 0 : 2; }
__host__ __device__ constexpr int o_nk(int t) { return (t == 2 || t == 4 || t == 6 || t >= 9) ? 3 : 2; }
__host__ __device__ constexpr int o_base(int t) { return t == 0 ? 0 : o_base(t - 1) + o_nk(t - 1); }

struct Params {
  const __nv_bfloat16* x;
  const __nv_bfloat16* wqkv;
  const __nv_bfloat16* wo;
  const __nv_bfloat16* w1;
  const __nv_bfloat16* w3;
  const __nv_bfloat16* w2;
  __nv_bfloat16* out;
};

__global__ void __launch_bounds__(NTHREADS, 1)
fused_block_kernel(const __grid_constant__ CUtensorMap m_qkv, const __grid_constant__ CUtensorMap m_w1,
                   const __grid_constant__ CUtensorMap m_w3, const __grid_constant__ CUtensorMap m_w2,
                   const __grid_constant__ CUtensorMap m_wo, const Params p) {
  extern __shared__ __align__(1024) uint8_t smem_raw[];
  const uint32_t sb = ((uint32_t)__cvta_generic_to_shared(smem_raw) + 1023u) & ~1023u;
  const int tid = threadIdx.x, warp = tid >> 5, lane = tid & 31;
  const int r = blockIdx.x >> 3, j = blockIdx.x & 7;

  if (warp < 8) {
    if (lane == 0) {
      mbar_init(sb + B_X + 8 * warp, 1);
      asm volatile("fence.mbarrier_init.release.cluster;\n" ::: "memory");
      fence_async_smem();
      mbar_expect(sb + B_X + 8 * warp, 16 * 1152);
    }
    __syncwarp();
    if (lane < 16) bulk_g2s(sb + HB + (warp * 16 + lane) * XPITCH, p.x + (size_t)(r * 128 + warp * 16 + lane) * D_, 1152, sb + B_X + 8 * warp);
  } else if (tid == 256) {
    for (int s = 0; s < 7; s++) { mbar_init(sb + B_FULL + 8 * s, 1); mbar_init(sb + B_EMPTY + 8 * s, 8); }
    asm volatile("fence.mbarrier_init.release.cluster;\n" ::: "memory");
    fence_async_smem();
    for (int s = 0; s < 6; s++) {
      mbar_expect(sb + B_FULL + 8 * s, SLOT);
      tma2d(sb + s * SLOT, &m_qkv, D_ + 72 * j, 96 * s, sb + B_FULL + 8 * s);
    }
  } else if (tid == 288) {
    mbar_init(sb + B_XDONE, 8);
    mbar_init(sb + B_LFULL, 96);
    mbar_init(sb + B_KVT, 8);
    mbar_init(sb + B_KVFREE, 3);
    mbar_init(sb + B_KVRDY, 3);
    mbar_init(sb + B_HFREE, 8);
    for (int s = 0; s < 16; s++) mbar_init(sb + B_PUB + 8 * s, 4);
    for (int s = 0; s < 14; s++) mbar_init(sb + B_PFULL + 8 * s, 1);
    asm volatile("fence.mbarrier_init.release.cluster;\n" ::: "memory");
    fence_async_smem();
  }
  __syncthreads();

  if (warp >= 8) {
    asm volatile("setmaxnreg.dec.sync.aligned.u32 40;\n");
    if (warp == 8) {
      if (lane == 0) {
        for (int n = 1; n < 30; n++) {
          const uint32_t ph = (n & 1) ^ 1;
          const int c = n == 21 ? 8 : ((j + n - 21) & 7);
          for (int s = 0; s < 6; s++) {
            const uint32_t fb = sb + B_FULL + 8 * s, dst = sb + s * SLOT;
            mbar_wait(sb + B_EMPTY + 8 * s, ph);
            mbar_expect(fb, SLOT);
            if (n == 1) tma2d(dst, &m_qkv, 2 * D_ + 72 * j, 96 * s, fb);
            else if (n < 20) {
              tma2d(dst, &m_w1, 576 * j + 32 * (n - 2), 96 * s, fb);
              tma2d(dst + SLOT / 2, &m_w3, 576 * j + 32 * (n - 2), 96 * s, fb);
            } else if (n == 20) tma2d(dst, &m_qkv, 72 * j, 96 * s, fb);
            else tma2d(dst, &m_w2, 64 * c, 576 * j + 96 * s, fb);
          }
          if (n >= 21) {
            if (n == 21) mbar_wait(sb + B_HFREE, 0);
            mbar_wait(sb + B_EMPTY + 48, n & 1);
            mbar_expect(sb + B_FULL + 48, 80 * 128);
            tma2d(sb + WO_SLOT, &m_wo, 64 * c, 72 * j, sb + B_FULL + 48);
          }
        }
      }
    } else {
      const int ht = tid - 288;
      const uint32_t ep = g_epoch[blockIdx.x] + 1;
      for (int i = ht; i < 36 * 3 * 2; i += 96) {
        const int row = 36 * r + i / 6, g = (i % 6) >> 1;
        prefetch_l2(p.wqkv + (size_t)row * (3 * D_) + g * D_ + 72 * j + (i & 1) * 64);
      }
      mbar_wait(sb + B_XDONE, 0);
      for (int i = ht; i < 3 * 576; i += 96) {
        const int g = i / 576, k = i - g * 576;
        const int col = (g == 2 ? 0 : (g + 1) * D_) + 72 * j + 64;
        asm volatile("cp.async.cg.shared.global [%0], [%1], 16;\n" ::"r"(sb + L24_T + i * 16), "l"(p.wqkv + (size_t)k * (3 * D_) + col) : "memory");
      }
      for (int cb = 0; cb < 9; cb++) {
        if (ht < 72) {
          const __nv_bfloat16* w = ht < 36 ? p.w1 : p.w3;
          const int row = 36 * r + (ht < 36 ? ht : ht - 36);
          prefetch_l2(w + (size_t)row * F_ + 576 * j + cb * 64);
        }
      }
      asm volatile("cp.async.wait_all;\n" ::: "memory");
      fence_async_smem();
      mbar_arrive(sb + B_LFULL);
      for (int i = ht; i < 36 * 9; i += 96) prefetch_l2(p.w2 + (size_t)(576 * j + 36 * r) * D_ + i * 64);
      if (r < 9 && ht < 72) prefetch_l2(p.wo + (size_t)(72 * j + 8 * r) * D_ + ht * 64);

      const int hw = warp - 9;
      mbar_wait(sb + B_KVT, 0);
      float4* kvp = g_kvp + (size_t)(j * 16 + r) * 864;
      for (int t = hw; t < 27; t += 3) {
        const int i = t < 3 ? 0 : t < 8 ? 1 : t < 13 ? 2 : t < 18 ? 3 : 4;
        const int u = t - kv_base(i) + kv_u0(i);
        float c[4] = {0.f, 0.f, 0.f, 0.f};
        const uint32_t aa = sb + V_T + ((lane & 7) + (lane >> 4) * 8) * 144 + (2 * i + (i < 4 ? ((lane >> 3) & 1) : 0)) * 16;
        const uint32_t ba = sb + PK_T + (lane & 15) * 144 + u * 16;
#pragma unroll 2
        for (int ks = 0; ks < 8; ks++) {
          uint32_t a0, a1, a2, a3, b0, b1;
          ldsm4t(a0, a1, a2, a3, aa + ks * 16 * 144);
          ldsm2t(b0, b1, ba + ks * 16 * 144);
          if (i == 4) { a1 = 0x3F803F80u; a3 = 0x3F803F80u; }
          mma16816(c, a0, a1, a2, a3, b0, b1);
        }
        kvp[t * 32 + lane] = make_float4(c[0], c[1], c[2], c[3]);
      }
      __syncwarp();
      if (lane == 0) mbar_arrive(sb + B_KVFREE);
      bar_sync(3, 96);
      if (ht == 0) { red_rel(&g_cnt1[j * 32]); wait_ge(&g_cnt1[j * 32], 16 * ep); }
      bar_sync(3, 96);
      if (ht < 54) {
        float4 s = make_float4(0.f, 0.f, 0.f, 0.f);
#pragma unroll 4
        for (int rr = 0; rr < 16; rr++) {
          const float4 v = __ldcg(g_kvp + (size_t)(j * 16 + rr) * 864 + r * 54 + ht);
          s.x += v.x; s.y += v.y; s.z += v.z; s.w += v.w;
        }
        g_kvs[j * 864 + r * 54 + ht] = s;
      }
      bar_sync(3, 96);
      if (ht == 0) { red_rel(&g_cnt2[j * 32]); wait_ge(&g_cnt2[j * 32], 16 * ep); }
      bar_sync(3, 96);
      {
        const int g = lane >> 2, q = lane & 3;
        for (int f = hw; f < 27; f += 3) {
          int t = 0;
          while (t < 10 && f >= o_base(t + 1)) t++;
          const int ks = o_k0(t) + f - o_base(t);
          const int i = t < 9 ? (t >> 1) : 4;
          const int half = t < 9 ? (t & 1) : 1;
          const int he = t < 9 ? (8 * t + g) / 18 : (t - 9) * 2 + (g & 1);
          uint32_t b[2];
#pragma unroll
          for (int z = 0; z < 2; z++) {
            const int u = 2 * ks + z;
            const int d = 8 * u + 2 * q;
            b[z] = 0;
            if (d < 72 && d / 18 == he) {
              const float2 v = __ldcg(reinterpret_cast<const float2*>(g_kvs + j * 864 + (kv_base(i) + u - kv_u0(i)) * 32 + lane) + half);
              b[z] = pack2(v.x, v.y);
            }
          }
          sts64(sb + KVF + f * 256 + lane * 8, b[0], b[1]);
        }
        __syncwarp();
        if (lane == 0) mbar_arrive(sb + B_KVRDY);
      }
      if (hw < 2) {
        if (lane == 0) {
          for (int s = 0; s < 8; s++) {
            const int c = s == 0 ? 8 : ((j + s) & 7);
            mbar_wait(sb + B_PUB + 16 * s + 8 * hw, 0);
            st_rel(&g_flag[((r * 9 + c) * 8 + j) * 2 + hw], ep);
          }
        }
      } else {
        if (lane < 8) wait_ge(&g_flag[((r * 9 + 8) * 8 + lane) * 2 + (j >> 2)], ep);
        __syncwarp();
        const int g = lane >> 2, q = lane & 3;
        const size_t ro = (size_t)(r * 128 + j * 16 + g) * D_ + 512 + 2 * q;
        for (int i = 0; i < 4; i++) {
          float s[8];
          {
            const uint32_t x0 = *reinterpret_cast<const uint32_t*>(p.x + ro + 16 * i), x1 = *reinterpret_cast<const uint32_t*>(p.x + ro + 8 * D_ + 16 * i);
            const uint32_t x2 = *reinterpret_cast<const uint32_t*>(p.x + ro + 16 * i + 8), x3 = *reinterpret_cast<const uint32_t*>(p.x + ro + 8 * D_ + 16 * i + 8);
            s[0] = blo(x0); s[1] = bhi(x0); s[2] = blo(x1); s[3] = bhi(x1); s[4] = blo(x2); s[5] = bhi(x2); s[6] = blo(x3); s[7] = bhi(x3);
          }
#pragma unroll 2
          for (int jj = 0; jj < 8; jj++) {
            const uint4 v = __ldcg(g_part + (size_t)(((r * 9 + 8) * 8 + jj) * 2 + (j >> 2)) * 512 + (j & 3) * 128 + i * 32 + lane);
            s[0] += blo(v.x); s[1] += bhi(v.x); s[2] += blo(v.y); s[3] += bhi(v.y); s[4] += blo(v.z); s[5] += bhi(v.z); s[6] += blo(v.w); s[7] += bhi(v.w);
          }
          *reinterpret_cast<uint32_t*>(p.out + ro + 16 * i) = pack2(s[0], s[1]);
          *reinterpret_cast<uint32_t*>(p.out + ro + 8 * D_ + 16 * i) = pack2(s[2], s[3]);
          *reinterpret_cast<uint32_t*>(p.out + ro + 16 * i + 8) = pack2(s[4], s[5]);
          *reinterpret_cast<uint32_t*>(p.out + ro + 8 * D_ + 16 * i + 8) = pack2(s[6], s[7]);
        }
        mbar_wait(sb + B_HFREE, 0);
        if (lane < 2) {
          for (int s = 1; s < 8; s++) {
            const int src = (j - s) & 7;
            const int idx = ((r * 9 + j) * 8 + src) * 2 + lane;
            uint32_t n = 0;
            while (ld_acq(&g_flag[idx]) != ep) { if (++n > SPIN_LIMIT) __trap(); }
            asm volatile("fence.proxy.async;\n" ::: "memory");
            const uint32_t fb = sb + B_PFULL + 16 * (s - 1) + 8 * lane;
            mbar_expect(fb, 8192);
            bulk_g2s(sb + (lane ? PS1 : PS0) + (s - 1) * 8192, g_part + (size_t)idx * 512, 8192, fb);
          }
        }
        if (lane == 0) g_epoch[blockIdx.x] = ep;
      }
    }
  } else {
    asm volatile("setmaxnreg.inc.sync.aligned.u32 232;\n");
    const int wg = warp >> 2;
    uint32_t a[36][4];
    float dA[32], dB[32];
    const bool l0 = lane == 0;
    const uint64_t dsw128 = mkdesc(sb, 16, 1024, 1);
    const uint64_t dsw64 = mkdesc(sb, SLOT / 2, 512, 2);

    auto stage = [&](float (&d)[32], const uint64_t dbase, const int kstride, const int s, const uint32_t ph, const int rel) {
      mbar_wait(sb + B_FULL + 8 * s, ph);
      wg_fence();
#pragma unroll
      for (int ks = 0; ks < 6; ks++) wgmma_rs64(d, a[s * 6 + ks], dbase + ((s * SLOT + ks * kstride) >> 4), (s | ks) != 0);
      wg_commit();
      wg_wait<1>();
      if (rel >= 0 && l0) mbar_arrive(sb + B_EMPTY + 8 * rel);
    };

    mbar_wait(sb + B_X + 8 * warp, 0);
    uint32_t mb0, mb1;
    float dm0, dm1;
    {
      const uint32_t xa = sb + HB + (warp * 16 + (lane & 15)) * XPITCH + (lane >> 4) * 16;
      float c[4][4];
#pragma unroll
      for (int i = 0; i < 4; i++) { c[i][0] = c[i][1] = c[i][2] = c[i][3] = 0.f; }
#pragma unroll
      for (int ks = 0; ks < 36; ks++) ldsm4(a[ks][0], a[ks][1], a[ks][2], a[ks][3], xa + ks * 32);
      __syncwarp();
      if (l0) mbar_arrive(sb + B_XDONE);
#pragma unroll
      for (int ks = 0; ks < 36; ks++) mma16816(c[ks & 3], a[ks][0], a[ks][1], a[ks][2], a[ks][3], 0x3F803F80u, 0x3F803F80u);
      const float m0 = ((c[0][0] + c[1][0]) + (c[2][0] + c[3][0])) * (1.f / 576.f);
      const float m1 = ((c[0][2] + c[1][2]) + (c[2][2] + c[3][2])) * (1.f / 576.f);
      mb0 = pack2(m0, m0);
      mb1 = pack2(m1, m1);
      dm0 = m0 - blo(mb0);
      dm1 = m1 - blo(mb1);
    }
    float ss0 = 0.f, ss1 = 0.f;
#pragma unroll
    for (int s = 0; s < 6; s++) {
#pragma unroll
      for (int ks = 6 * s; ks < 6 * s + 6; ks++) {
        a[ks][0] = bsub2(a[ks][0], mb0); a[ks][1] = bsub2(a[ks][1], mb1);
        a[ks][2] = bsub2(a[ks][2], mb0); a[ks][3] = bsub2(a[ks][3], mb1);
        float t;
        t = blo(a[ks][0]); ss0 = fmaf(t, t, ss0); t = bhi(a[ks][0]); ss0 = fmaf(t, t, ss0);
        t = blo(a[ks][1]); ss1 = fmaf(t, t, ss1); t = bhi(a[ks][1]); ss1 = fmaf(t, t, ss1);
        t = blo(a[ks][2]); ss0 = fmaf(t, t, ss0); t = bhi(a[ks][2]); ss0 = fmaf(t, t, ss0);
        t = blo(a[ks][3]); ss1 = fmaf(t, t, ss1); t = bhi(a[ks][3]); ss1 = fmaf(t, t, ss1);
      }
      asm volatile("" : "+f"(ss0), "+f"(ss1)::"memory");
      stage(dA, dsw128, 2048, s, 0, s - 1);
    }
    ss0 += __shfl_xor_sync(0xffffffffu, ss0, 1); ss1 += __shfl_xor_sync(0xffffffffu, ss1, 1);
    ss0 += __shfl_xor_sync(0xffffffffu, ss0, 2); ss1 += __shfl_xor_sync(0xffffffffu, ss1, 2);
    const float r0 = 1.f / rbf(sqrtf(rbf(rbf(fmaxf(ss0 * (1.f / 576.f) - dm0 * dm0, 0.f)) + 1e-5f)));
    const float r1 = 1.f / rbf(sqrtf(rbf(rbf(fmaxf(ss1 * (1.f / 576.f) - dm1 * dm1, 0.f)) + 1e-5f)));

    const uint32_t tile_off = (warp * 16 + (lane & 15)) * 144 + (lane >> 4) * 16;
    stage(dB, dsw128, 2048, 0, 1, 5);
    pin(dA);
    mbar_wait(sb + B_XDONE, 0);
#pragma unroll
    for (int t = 0; t < 8; t += 2)
      stsm4(sb + PK_T + tile_off + t * 16, pack2(phi(dA[4 * t] * r0), phi(dA[4 * t + 1] * r0)), pack2(phi(dA[4 * t + 2] * r1), phi(dA[4 * t + 3] * r1)),
            pack2(phi(dA[4 * t + 4] * r0), phi(dA[4 * t + 5] * r0)), pack2(phi(dA[4 * t + 6] * r1), phi(dA[4 * t + 7] * r1)));
#pragma unroll
    for (int s = 1; s < 6; s++) stage(dB, dsw128, 2048, s, 1, s - 1);
    {
      float dL[12];
      const uint64_t dl = mkdesc(sb + L24_T, 128, 576 * 16, 0);
      mbar_wait(sb + B_LFULL, 0);
      wg_fence();
#pragma unroll
      for (int ks = 0; ks < 6; ks++) wgmma_rs24(dL, a[ks], dl + ks * 16, ks != 0);
      wg_commit();
      wg_wait<1>();
      if (l0) mbar_arrive(sb + B_EMPTY + 8 * 5);
#pragma unroll
      for (int ks = 6; ks < 36; ks++) wgmma_rs24(dL, a[ks], dl + ks * 16, 1);
      wg_commit();
      pin(dB);
#pragma unroll
      for (int t = 0; t < 8; t += 2)
        stsm4(sb + V_T + tile_off + t * 16, pack2(dB[4 * t] * r0, dB[4 * t + 1] * r0), pack2(dB[4 * t + 2] * r1, dB[4 * t + 3] * r1),
              pack2(dB[4 * t + 4] * r0, dB[4 * t + 5] * r0), pack2(dB[4 * t + 6] * r1, dB[4 * t + 7] * r1));
      stage(dB, dsw64, 1024, 0, 0, -1);
      pin(dL);
      const uint32_t lo = (warp * 16 + (lane >> 2)) * 144 + 128 + (lane & 3) * 4;
      sts32(sb + PK_T + lo, pack2(phi(dL[0] * r0), phi(dL[1] * r0)));
      sts32(sb + PK_T + lo + 8 * 144, pack2(phi(dL[2] * r1), phi(dL[3] * r1)));
      sts32(sb + V_T + lo, pack2(dL[4] * r0, dL[5] * r0));
      sts32(sb + V_T + lo + 8 * 144, pack2(dL[6] * r1, dL[7] * r1));
      sts64(sb + Q8 + tid * 8, pack2(phi(dL[8] * r0), phi(dL[9] * r0)), pack2(phi(dL[10] * r1), phi(dL[11] * r1)));
      __syncwarp();
      if (l0) mbar_arrive(sb + B_KVT);
    }
    uint32_t hs = sb + HB + wg * HHALF + (tid & 127) * 16;
    auto epiF = [&](float (&d)[32]) {
      pin(d);
      const float e0 = r0 * -1.4426950408889634f, e1 = r1 * -1.4426950408889634f, q0 = r0 * r0, q1 = r1 * r1;
      uint32_t h[8];
#pragma unroll
      for (int i = 0; i < 8; i++) {
        const float e = (i & 1) ? e1 : e0, q = (i & 1) ? q1 : q0;
        const float g0 = d[2 * i], g1 = d[2 * i + 1];
        h[i] = pack2(g0 * d[2 * i + 16] * q * rcp(1.f + ex2(g0 * e)), g1 * d[2 * i + 17] * q * rcp(1.f + ex2(g1 * e)));
      }
      sts128(hs, h[0], h[1], h[2], h[3]);
      sts128(hs + 2048, h[4], h[5], h[6], h[7]);
      hs += 4096;
    };
#pragma unroll 1
    for (int it = 0; it < 8; it++) {
#pragma unroll
      for (int s = 1; s < 6; s++) stage(dB, dsw64, 1024, s, 0, s - 1);
      stage(dA, dsw64, 1024, 0, 1, 5);
      if (it == 4) mbar_wait(sb + B_KVFREE, 0);
      epiF(dB);
#pragma unroll
      for (int s = 1; s < 6; s++) stage(dA, dsw64, 1024, s, 1, s - 1);
      stage(dB, dsw64, 1024, 0, 0, 5);
      epiF(dA);
    }
#pragma unroll
    for (int s = 1; s < 6; s++) stage(dB, dsw64, 1024, s, 0, s - 1);
    stage(dA, dsw64, 1024, 0, 1, 5);
    epiF(dB);
#pragma unroll
    for (int s = 1; s < 6; s++) stage(dA, dsw64, 1024, s, 1, s - 1);
    stage(dB, dsw128, 2048, 0, 0, 5);
    epiF(dA);
    hs -= 18 * 4096;
#pragma unroll
    for (int s = 1; s < 6; s++) {
      stage(dB, dsw128, 2048, s, 0, s - 1);
#pragma unroll
      for (int ks = 6 * s - 6; ks < 6 * s; ks++) lds128(a[ks][0], a[ks][1], a[ks][2], a[ks][3], hs + ks * 2048);
    }
    const uint32_t ot = sb + (wg ? OT1 : OT0);
    const uint64_t do_a = mkdesc(ot, 128, 1280, 0);
    const uint64_t do_b = mkdesc(sb + WO_SLOT, 16, 1024, 1);
    auto stageO = [&](float (&d)[32], const uint32_t ph) {
      mbar_wait(sb + B_FULL + 48, ph);
      wg_fence();
#pragma unroll
      for (int ks = 0; ks < 5; ks++) wgmma_ss64(d, do_a + ks * 16, do_b + ks * 128);
      wg_commit();
      wg_wait<1>();
      if (l0) mbar_arrive(sb + B_EMPTY + 8 * 5);
    };
    auto epiP = [&](float (&d)[32], const int step) {
      pin(d);
      const int c = step == 0 ? 8 : ((j + step) & 7);
      uint4* dst = g_part + (size_t)(((r * 9 + c) * 8 + j) * 2 + wg) * 512 + (warp & 3) * 128 + lane;
#pragma unroll
      for (int i = 0; i < 4; i++)
        __stcg(dst + i * 32, make_uint4(pack2(d[8 * i], d[8 * i + 1]), pack2(d[8 * i + 2], d[8 * i + 3]), pack2(d[8 * i + 4], d[8 * i + 5]), pack2(d[8 * i + 6], d[8 * i + 7])));
      __syncwarp();
      if (l0) mbar_arrive(sb + B_PUB + 16 * step + 8 * wg);
    };
    stage(dA, dsw128, 2048, 0, 1, 5);
#pragma unroll
    for (int ks = 30; ks < 36; ks++) lds128(a[ks][0], a[ks][1], a[ks][2], a[ks][3], hs + ks * 2048);
    {
      pin(dB);
      uint32_t pq[18];
#pragma unroll
      for (int i = 0; i < 16; i++) {
        const float rr = (i & 1) ? r1 : r0;
        pq[i] = pack2(phi(dB[2 * i] * rr), phi(dB[2 * i + 1] * rr));
      }
      lds64(pq[16], pq[17], sb + Q8 + tid * 8);
      fence_async_smem();
      __syncwarp();
      if (l0) mbar_arrive(sb + B_HFREE);
      stage(dA, dsw128, 2048, 1, 1, 0);
      mbar_wait(sb + B_KVRDY, 0);
      bar_sync(1 + wg, 128);
      const uint32_t fa = sb + KVF + lane * 8;
      auto omma = [&](float (&c)[4], const int t) {
        c[0] = c[1] = c[2] = c[3] = 0.f;
#pragma unroll
        for (int z = 0; z < o_nk(t); z++) {
          const int ks = o_k0(t) + z;
          uint32_t b0, b1;
          lds64(b0, b1, fa + (o_base(t) + z) * 256);
          if (ks < 4) mma16816(c, pq[4 * ks], pq[4 * ks + 1], pq[4 * ks + 2], pq[4 * ks + 3], b0, b1);
          else mma16816(c, pq[16], pq[17], 0u, 0u, b0, b1);
        }
      };
      float iv[4][2];
      {
        float cx[4], cy[4];
        omma(cx, 9);
        omma(cy, 10);
        iv[0][0] = 1.f / (cx[0] + 1e-6f); iv[1][0] = 1.f / (cx[1] + 1e-6f); iv[0][1] = 1.f / (cx[2] + 1e-6f); iv[1][1] = 1.f / (cx[3] + 1e-6f);
        iv[2][0] = 1.f / (cy[0] + 1e-6f); iv[3][0] = 1.f / (cy[1] + 1e-6f); iv[2][1] = 1.f / (cy[2] + 1e-6f); iv[3][1] = 1.f / (cy[3] + 1e-6f);
      }
      const int q = lane & 3;
      const uint32_t oa = ot + ((warp & 3) * 2 + ((lane >> 3) & 1)) * 1280 + (lane >> 4) * 128 + (lane & 7) * 16;
#pragma unroll
      for (int t = 0; t < 10; t += 2) {
        uint32_t o[4];
#pragma unroll
        for (int z = 0; z < 2; z++) {
          const int tt = t + z;
          if (tt < 9) {
            float c[4];
            omma(c, tt);
            const int hl = (8 * tt) / 18, hh = (8 * tt + 7) / 18;
            const bool up = hl != hh && 8 * tt + 2 * q >= 18 * hh;
            const float i0 = up ? iv[hh][0] : iv[hl][0], i1 = up ? iv[hh][1] : iv[hl][1];
            o[2 * z] = pack2(c[0] * i0, c[1] * i0);
            o[2 * z + 1] = pack2(c[2] * i1, c[3] * i1);
          } else {
            o[2 * z] = 0; o[2 * z + 1] = 0;
          }
        }
        stsm4(oa + t * 128, o[0], o[1], o[2], o[3]);
        if (t == 2) stage(dA, dsw128, 2048, 2, 1, 1);
      }
      fence_async_smem();
    }
#pragma unroll
    for (int s = 3; s < 6; s++) stage(dA, dsw128, 2048, s, 1, s - 1);
    bar_sync(1 + wg, 128);
    stageO(dA, 0);
    stage(dB, dsw128, 2048, 0, 0, 6);
    epiP(dA, 0);
#pragma unroll 1
    for (int it = 0; it < 3; it++) {
#pragma unroll
      for (int s = 1; s < 6; s++) stage(dB, dsw128, 2048, s, 0, s - 1);
      stageO(dB, 1);
      stage(dA, dsw128, 2048, 0, 1, 6);
      epiP(dB, 1 + 2 * it);
#pragma unroll
      for (int s = 1; s < 6; s++) stage(dA, dsw128, 2048, s, 1, s - 1);
      stageO(dA, 0);
      stage(dB, dsw128, 2048, 0, 0, 6);
      epiP(dA, 2 + 2 * it);
    }
#pragma unroll
    for (int s = 1; s < 6; s++) stage(dB, dsw128, 2048, s, 0, s - 1);
    stageO(dB, 1);
    stage(dA, dsw128, 2048, 0, 1, 6);
    epiP(dB, 7);
    {
      const __nv_bfloat16* xp = p.x + (size_t)(r * 128 + warp * 16 + (lane >> 2)) * D_ + 64 * j + 2 * (lane & 3);
      uint32_t xv[16];
#pragma unroll
      for (int t = 0; t < 8; t++) {
        xv[2 * t] = __ldg(reinterpret_cast<const uint32_t*>(xp + 8 * t));
        xv[2 * t + 1] = __ldg(reinterpret_cast<const uint32_t*>(xp + 8 * D_ + 8 * t));
      }
      stage(dA, dsw128, 2048, 1, 1, -1);
#pragma unroll
      for (int i = 0; i < 16; i++) { dB[2 * i] = blo(xv[i]); dB[2 * i + 1] = bhi(xv[i]); }
    }
    const uint32_t ps = sb + (wg ? PS1 : PS0) + (warp & 3) * 2048;
    auto addp = [&](const int s) {
      mbar_wait(sb + B_PFULL + 16 * s + 8 * wg, 0);
#pragma unroll
      for (int i = 0; i < 4; i++) {
        uint32_t v0, v1, v2, v3;
        lds128(v0, v1, v2, v3, ps + s * 8192 + i * 512 + lane * 16);
        dB[8 * i] += blo(v0); dB[8 * i + 1] += bhi(v0); dB[8 * i + 2] += blo(v1); dB[8 * i + 3] += bhi(v1);
        dB[8 * i + 4] += blo(v2); dB[8 * i + 5] += bhi(v2); dB[8 * i + 6] += blo(v3); dB[8 * i + 7] += bhi(v3);
      }
      pin(dB);
    };
    addp(0);
    stage(dA, dsw128, 2048, 2, 1, -1);
    addp(1); addp(2);
    stage(dA, dsw128, 2048, 3, 1, -1);
    addp(3);
    stage(dA, dsw128, 2048, 4, 1, -1);
    addp(4);
    stage(dA, dsw128, 2048, 5, 1, -1);
    addp(5);
    stageO(dA, 0);
    addp(6);
    wg_wait<0>();
    pin(dA);
    {
      __syncwarp();
      const int row = lane & 15;
#pragma unroll
      for (int t = 0; t < 8; t += 2)
        stsm4(ps + row * 128 + (((t + (lane >> 4)) ^ (row & 7)) << 4),
              pack2(dA[4 * t] + dB[4 * t], dA[4 * t + 1] + dB[4 * t + 1]), pack2(dA[4 * t + 2] + dB[4 * t + 2], dA[4 * t + 3] + dB[4 * t + 3]),
              pack2(dA[4 * t + 4] + dB[4 * t + 4], dA[4 * t + 5] + dB[4 * t + 5]), pack2(dA[4 * t + 6] + dB[4 * t + 6], dA[4 * t + 7] + dB[4 * t + 7]));
      __syncwarp();
#pragma unroll
      for (int i = 0; i < 4; i++) {
        const int rr = i * 4 + (lane >> 3), ch = lane & 7;
        uint4 v;
        lds128(v.x, v.y, v.z, v.w, ps + rr * 128 + ((ch ^ (rr & 7)) << 4));
        *reinterpret_cast<uint4*>(p.out + (size_t)(r * 128 + warp * 16 + rr) * D_ + 64 * j + ch * 8) = v;
      }
    }
  }
}

typedef CUresult (*EncodeFn)(CUtensorMap*, CUtensorMapDataType, cuuint32_t, void*, const cuuint64_t*, const cuuint64_t*, const cuuint32_t*,
                             const cuuint32_t*, CUtensorMapInterleave, CUtensorMapSwizzle, CUtensorMapL2promotion, CUtensorMapFloatOOBfill);

CUtensorMap make_map(EncodeFn enc, const void* ptr, int rows, int cols, int brow, int bcol, CUtensorMapSwizzle sw) {
  CUtensorMap m;
  cuuint64_t gd[2] = {(cuuint64_t)cols, (cuuint64_t)rows};
  cuuint64_t gs[1] = {(cuuint64_t)cols * 2};
  cuuint32_t bd[2] = {(cuuint32_t)bcol, (cuuint32_t)brow};
  cuuint32_t es[2] = {1, 1};
  enc(&m, CU_TENSOR_MAP_DATA_TYPE_BFLOAT16, 2, const_cast<void*>(ptr), gd, gs, bd, es, CU_TENSOR_MAP_INTERLEAVE_NONE, sw,
      CU_TENSOR_MAP_L2_PROMOTION_L2_128B, CU_TENSOR_MAP_FLOAT_OOB_FILL_NONE);
  return m;
}

}

extern "C" void kernel_launch(void* const* d_in, const int* in_sizes, int n_in, void* d_out, int out_size) {
  (void)in_sizes; (void)n_in; (void)out_size;
  static EncodeFn enc = nullptr;
  if (!enc) {
    cudaDriverEntryPointQueryResult qr;
    cudaGetDriverEntryPoint("cuTensorMapEncodeTiled", (void**)&enc, cudaEnableDefault, &qr);
    cudaFuncSetAttribute(fused_block_kernel, cudaFuncAttributeMaxDynamicSharedMemorySize, SMEM_BYTES);
  }
  Params p;
  p.x = (const __nv_bfloat16*)d_in[0];
  p.wqkv = (const __nv_bfloat16*)d_in[1];
  p.wo = (const __nv_bfloat16*)d_in[2];
  p.w1 = (const __nv_bfloat16*)d_in[4];
  p.w3 = (const __nv_bfloat16*)d_in[5];
  p.w2 = (const __nv_bfloat16*)d_in[6];
  p.out = (__nv_bfloat16*)d_out;
  const CUtensorMap m_qkv = make_map(enc, p.wqkv, D_, 3 * D_, 96, 64, CU_TENSOR_MAP_SWIZZLE_128B);
  const CUtensorMap m_w1 = make_map(enc, p.w1, D_, F_, 96, 32, CU_TENSOR_MAP_SWIZZLE_64B);
  const CUtensorMap m_w3 = make_map(enc, p.w3, D_, F_, 96, 32, CU_TENSOR_MAP_SWIZZLE_64B);
  const CUtensorMap m_w2 = make_map(enc, p.w2, F_, D_, 96, 64, CU_TENSOR_MAP_SWIZZLE_128B);
  const CUtensorMap m_wo = make_map(enc, p.wo, D_, D_, 80, 64, CU_TENSOR_MAP_SWIZZLE_128B);
  fused_block_kernel<<<128, NTHREADS, SMEM_BYTES>>>(m_qkv, m_w1, m_w3, m_w2, m_wo, p);
}
```

```cpp
#include <cuda_runtime.h>
#include <cuda.h>
#include <cuda_bf16.h>
#include <stdint.h>

namespace {

constexpr int D_ = 576, F_ = 4608;
constexpr int NTHREADS = 384;

constexpr uint32_t SLOT = 12288;
constexpr uint32_t HB = 6 * SLOT;
constexpr uint32_t HHALF = 73728;
constexpr uint32_t XPITCH = 1168;
constexpr uint32_t PK_T = HB + 36864;
constexpr uint32_t V_T = HB + 55296;
constexpr uint32_t L24_T = HB + HHALF + 46080;
constexpr uint32_t WO_SLOT = HB + 67584;
constexpr uint32_t OT0 = HB, OT1 = HB + 137216;
constexpr uint32_t PS0 = HB + 10240, PS1 = HB + 79872;
constexpr uint32_t KVF = HB + 2 * HHALF;
constexpr uint32_t Q8 = KVF + 6912;
constexpr uint32_t BARS = Q8 + 2048;
constexpr uint32_t SMEM_BYTES = BARS + 512;

constexpr uint32_t B_FULL = BARS;
constexpr uint32_t B_EMPTY = BARS + 56;
constexpr uint32_t B_X = BARS + 112;
constexpr uint32_t B_XDONE = BARS + 176;
constexpr uint32_t B_LFULL = BARS + 184;
constexpr uint32_t B_KVT = BARS + 192;
constexpr uint32_t B_KVFREE = BARS + 200;
constexpr uint32_t B_KVRDY = BARS + 208;
constexpr uint32_t B_HFREE = BARS + 216;
constexpr uint32_t B_PUB = BARS + 224;
constexpr uint32_t B_PFULL = BARS + 352;

constexpr uint32_t SPIN_LIMIT = 1u << 22;

__device__ uint4 g_part[16 * 9 * 8 * 2 * 512];
__device__ float4 g_kvp[8 * 16 * 360];
__device__ __align__(16) float g_kvs[8 * 1440];
__device__ uint32_t g_cnt1[8 * 32], g_cnt2[8 * 32];
__device__ uint32_t g_flag[16 * 9 * 8 * 2];
__device__ uint32_t g_epoch[128];

__device__ __forceinline__ void wg_fence() { asm volatile("wgmma.fence.sync.aligned;\n" ::: "memory"); }
__device__ __forceinline__ void wg_commit() { asm volatile("wgmma.commit_group.sync.aligned;\n" ::: "memory"); }
template <int N> __device__ __forceinline__ void wg_wait() { asm volatile("wgmma.wait_group.sync.aligned %0;\n" ::"n"(N) : "memory"); }
__host__ __device__ constexpr uint64_t mkdesc(uint32_t addr, uint32_t lbo, uint32_t sbo, uint32_t sw) {
  return (uint64_t)((addr & 0x3FFFF) >> 4) | ((uint64_t)(lbo >> 4) << 16) | ((uint64_t)(sbo >> 4) << 32) | ((uint64_t)sw << 62);
}
__device__ __forceinline__ void mbar_init(uint32_t a, uint32_t c) { asm volatile("mbarrier.init.shared::cta.b64 [%0], %1;\n" ::"r"(a), "r"(c) : "memory"); }
__device__ __forceinline__ void mbar_expect(uint32_t a, uint32_t b) { asm volatile("mbarrier.arrive.expect_tx.shared::cta.b64 _, [%0], %1;\n" ::"r"(a), "r"(b) : "memory"); }
__device__ __forceinline__ void mbar_arrive(uint32_t a) { asm volatile("mbarrier.arrive.shared::cta.b64 _, [%0];\n" ::"r"(a) : "memory"); }
__device__ __forceinline__ void mbar_wait(uint32_t a, uint32_t ph) {
  asm volatile(
      "{\n.reg .pred p;\n.reg .u32 n;\n"
      "mbarrier.try_wait.parity.shared::cta.b64 p, [%0], %1;\n"
      "@p bra DONE;\n"
      "mov.u32 n, 0;\n"
      "LOOP:\n"
      "mbarrier.try_wait.parity.shared::cta.b64 p, [%0], %1;\n"
      "@p bra DONE;\n"
      "add.u32 n, n, 1;\n"
      "setp.lt.u32 p, n, %2;\n"
      "@p bra LOOP;\n"
      "trap;\n"
      "DONE:\n}\n" ::"r"(a), "r"(ph), "n"(SPIN_LIMIT) : "memory");
}
__device__ __forceinline__ void tma2d(uint32_t dst, const CUtensorMap* m, int c0, int c1, uint32_t bar) {
  asm volatile("cp.async.bulk.tensor.2d.shared::cluster.global.mbarrier::complete_tx::bytes [%0], [%1, {%3, %4}], [%2];\n" ::"r"(dst), "l"(m), "r"(bar), "r"(c0), "r"(c1) : "memory");
}
__device__ __forceinline__ void bulk_g2s(uint32_t dst, const void* src, uint32_t bytes, uint32_t bar) {
  asm volatile("cp.async.bulk.shared::cluster.global.mbarrier::complete_tx::bytes [%0], [%1], %2, [%3];\n" ::"r"(dst), "l"(src), "r"(bytes), "r"(bar) : "memory");
}
__device__ __forceinline__ void prefetch_l2(const void* p) { asm volatile("prefetch.global.L2 [%0];\n" ::"l"(p)); }
__device__ __forceinline__ void fence_async_smem() { asm volatile("fence.proxy.async.shared::cta;\n" ::: "memory"); }
__device__ __forceinline__ void bar_sync(int id, int n) { asm volatile("bar.sync %0, %1;\n" ::"r"(id), "r"(n) : "memory"); }
__device__ __forceinline__ void ldsm4(uint32_t& r0, uint32_t& r1, uint32_t& r2, uint32_t& r3, uint32_t a) {
  asm volatile("ldmatrix.sync.aligned.m8n8.x4.shared.b16 {%0,%1,%2,%3}, [%4];\n" : "=r"(r0), "=r"(r1), "=r"(r2), "=r"(r3) : "r"(a) : "memory");
}
__device__ __forceinline__ void stsm4(uint32_t a, uint32_t r0, uint32_t r1, uint32_t r2, uint32_t r3) {
  asm volatile("stmatrix.sync.aligned.m8n8.x4.shared.b16 [%0], {%1,%2,%3,%4};\n" ::"r"(a), "r"(r0), "r"(r1), "r"(r2), "r"(r3) : "memory");
}
__device__ __forceinline__ void sts128(uint32_t a, uint32_t r0, uint32_t r1, uint32_t r2, uint32_t r3) {
  asm volatile("st.shared.v4.b32 [%0], {%1,%2,%3,%4};\n" ::"r"(a), "r"(r0), "r"(r1), "r"(r2), "r"(r3) : "memory");
}
__device__ __forceinline__ void lds128(uint32_t& r0, uint32_t& r1, uint32_t& r2, uint32_t& r3, uint32_t a) {
  asm volatile("ld.shared.v4.b32 {%0,%1,%2,%3}, [%4];\n" : "=r"(r0), "=r"(r1), "=r"(r2), "=r"(r3) : "r"(a) : "memory");
}
__device__ __forceinline__ void sts64(uint32_t a, uint32_t r0, uint32_t r1) { asm volatile("st.shared.v2.b32 [%0], {%1,%2};\n" ::"r"(a), "r"(r0), "r"(r1) : "memory"); }
__device__ __forceinline__ void lds64(uint32_t& r0, uint32_t& r1, uint32_t a) { asm volatile("ld.shared.v2.b32 {%0,%1}, [%2];\n" : "=r"(r0), "=r"(r1) : "r"(a) : "memory"); }
__device__ __forceinline__ uint32_t lds32(uint32_t a) { uint32_t v; asm volatile("ld.shared.b32 %0, [%1];\n" : "=r"(v) : "r"(a) : "memory"); return v; }
__device__ __forceinline__ void sts32(uint32_t a, uint32_t r0) { asm volatile("st.shared.b32 [%0], %1;\n" ::"r"(a), "r"(r0) : "memory"); }
__device__ __forceinline__ void mma16816(float (&c)[4], uint32_t a0, uint32_t a1, uint32_t a2, uint32_t a3, uint32_t b0, uint32_t b1) {
  asm volatile("mma.sync.aligned.m16n8k16.row.col.f32.bf16.bf16.f32 {%0,%1,%2,%3}, {%4,%5,%6,%7}, {%8,%9}, {%0,%1,%2,%3};\n"
               : "+f"(c[0]), "+f"(c[1]), "+f"(c[2]), "+f"(c[3]) : "r"(a0), "r"(a1), "r"(a2), "r"(a3), "r"(b0), "r"(b1));
}
__device__ __forceinline__ uint32_t pack2(float lo, float hi) {
  uint32_t r;
  asm("cvt.rn.bf16x2.f32 %0, %1, %2;\n" : "=r"(r) : "f"(hi), "f"(lo));
  return r;
}
__device__ __forceinline__ float blo(uint32_t w) { return __uint_as_float(w << 16); }
__device__ __forceinline__ float bhi(uint32_t w) { return __uint_as_float(w & 0xffff0000u); }
__device__ __forceinline__ float rbf(float x) { return __bfloat162float(__float2bfloat16_rn(x)); }
__device__ __forceinline__ float ex2(float x) { float r; asm("ex2.approx.ftz.f32 %0, %1;\n" : "=f"(r) : "f"(x)); return r; }
__device__ __forceinline__ float rcp(float x) { float r; asm("rcp.approx.ftz.f32 %0, %1;\n" : "=f"(r) : "f"(x)); return r; }
__device__ __forceinline__ float sqrta(float x) { float r; asm("sqrt.approx.ftz.f32 %0, %1;\n" : "=f"(r) : "f"(x)); return r; }
__device__ __forceinline__ uint32_t bsub2(uint32_t a, uint32_t b) { uint32_t r; asm("sub.rn.bf16x2 %0, %1, %2;\n" : "=r"(r) : "r"(a), "r"(b)); return r; }
__device__ __forceinline__ uint32_t ld_acq(const uint32_t* p) { uint32_t v; asm volatile("ld.acquire.gpu.global.u32 %0, [%1];\n" : "=r"(v) : "l"(p) : "memory"); return v; }
__device__ __forceinline__ void st_rel(uint32_t* p, uint32_t v) { asm volatile("st.release.gpu.global.u32 [%0], %1;\n" ::"l"(p), "r"(v) : "memory"); }
__device__ __forceinline__ void red_rel(uint32_t* p) { asm volatile("red.release.gpu.global.add.u32 [%0], 1;\n" ::"l"(p) : "memory"); }
__device__ __forceinline__ void wait_ge(const uint32_t* p, uint32_t target) {
  uint32_t n = 0;
  while ((int32_t)(ld_acq(p) - target) < 0) {
    __nanosleep(64);
    if (++n > SPIN_LIMIT) __trap();
  }
}
__device__ __forceinline__ float phi(float t) { return (t > 0.f ? t + 1.f : ex2(t * 1.4426950408889634f)) + 1e-6f; }

#define ACC8(d, o) "+f"(d[o + 0]), "+f"(d[o + 1]), "+f"(d[o + 2]), "+f"(d[o + 3]), "+f"(d[o + 4]), "+f"(d[o + 5]), "+f"(d[o + 6]), "+f"(d[o + 7])
#define REGS32 "{%0,%1,%2,%3,%4,%5,%6,%7,%8,%9,%10,%11,%12,%13,%14,%15,%16,%17,%18,%19,%20,%21,%22,%23,%24,%25,%26,%27,%28,%29,%30,%31}"
__device__ __forceinline__ void wgmma_rs64(float (&d)[32], const uint32_t (&a)[4], uint64_t db, int acc) {
  asm volatile("{\n.reg .pred p;\nsetp.ne.b32 p, %37, 0;\n"
               "wgmma.mma_async.sync.aligned.m64n64k16.f32.bf16.bf16 " REGS32 ", {%32,%33,%34,%35}, %36, p, 1, 1, 1;\n}\n"
               : ACC8(d, 0), ACC8(d, 8), ACC8(d, 16), ACC8(d, 24)
               : "r"(a[0]), "r"(a[1]), "r"(a[2]), "r"(a[3]), "l"(db), "r"(acc));
}
__device__ __forceinline__ void wgmma_ss64(float (&d)[32], uint64_t da, uint64_t db) {
  asm volatile("wgmma.mma_async.sync.aligned.m64n64k16.f32.bf16.bf16 " REGS32 ", %32, %33, 1, 1, 1, 0, 1;\n"
               : ACC8(d, 0), ACC8(d, 8), ACC8(d, 16), ACC8(d, 24)
               : "l"(da), "l"(db));
}
__device__ __forceinline__ void wgmma_rs24(float (&d)[12], const uint32_t (&a)[4], uint64_t db, int acc) {
  asm volatile("{\n.reg .pred p;\nsetp.ne.b32 p, %17, 0;\n"
               "wgmma.mma_async.sync.aligned.m64n24k16.f32.bf16.bf16 {%0,%1,%2,%3,%4,%5,%6,%7,%8,%9,%10,%11}, {%12,%13,%14,%15}, %16, p, 1, 1, 1;\n}\n"
               : ACC8(d, 0), "+f"(d[8]), "+f"(d[9]), "+f"(d[10]), "+f"(d[11])
               : "r"(a[0]), "r"(a[1]), "r"(a[2]), "r"(a[3]), "l"(db), "r"(acc));
}
template <int N> __device__ __forceinline__ void pin(float (&d)[N]) {
#pragma unroll
  for (int i = 0; i < N; i++) asm volatile("" : "+f"(d[i])::"memory");
}

__host__ __device__ constexpr int o_k0(int t) { return t <= 2 ? 0 : t <= 4 ? 1 : t <= 6 ? 2 : t <= 8 ? 3 : t == 9 ? 0 : 2; }
__host__ __device__ constexpr int o_nk(int t) { return (t == 2 || t == 4 || t == 6 || t >= 9) ? 3 : 2; }
__host__ __device__ constexpr int o_base(int t) { return t == 0 ? 0 : o_base(t - 1) + o_nk(t - 1); }

struct Params {
  const __nv_bfloat16* x;
  const __nv_bfloat16* wqkv;
  const __nv_bfloat16* wo;
  const __nv_bfloat16* w1;
  const __nv_bfloat16* w3;
  const __nv_bfloat16* w2;
  __nv_bfloat16* out;
};

__global__ void __launch_bounds__(NTHREADS, 1)
fused_block_kernel(const __grid_constant__ CUtensorMap m_qkv, const __grid_constant__ CUtensorMap m_w1,
                   const __grid_constant__ CUtensorMap m_w3, const __grid_constant__ CUtensorMap m_w2,
                   const __grid_constant__ CUtensorMap m_wo, const Params p) {
  extern __shared__ __align__(1024) uint8_t smem_raw[];
  constexpr uint32_t sb = 1024;
  if ((uint32_t)__cvta_generic_to_shared(smem_raw) != sb) __trap();
  const int tid = threadIdx.x, warp = tid >> 5, lane = tid & 31;
  const int r = blockIdx.x >> 3, j = blockIdx.x & 7;

  if (warp < 8) {
    if (lane == 0) {
      mbar_init(sb + B_X + 8 * warp, 1);
      asm volatile("fence.mbarrier_init.release.cluster;\n" ::: "memory");
      fence_async_smem();
      mbar_expect(sb + B_X + 8 * warp, 16 * 1152);
    }
    __syncwarp();
    if (lane < 16) bulk_g2s(sb + HB + (warp * 16 + lane) * XPITCH, p.x + (size_t)(r * 128 + warp * 16 + lane) * D_, 1152, sb + B_X + 8 * warp);
  } else if (tid == 256) {
    for (int s = 0; s < 7; s++) { mbar_init(sb + B_FULL + 8 * s, 1); mbar_init(sb + B_EMPTY + 8 * s, 8); }
    asm volatile("fence.mbarrier_init.release.cluster;\n" ::: "memory");
    fence_async_smem();
    for (int s = 0; s < 6; s++) {
      mbar_expect(sb + B_FULL + 8 * s, SLOT);
      tma2d(sb + s * SLOT, &m_qkv, D_ + 72 * j, 96 * s, sb + B_FULL + 8 * s);
    }
  } else if (tid == 288) {
    mbar_init(sb + B_XDONE, 8);
    mbar_init(sb + B_LFULL, 96);
    mbar_init(sb + B_KVT, 8);
    mbar_init(sb + B_KVFREE, 3);
    mbar_init(sb + B_KVRDY, 3);
    mbar_init(sb + B_HFREE, 8);
    for (int s = 0; s < 16; s++) mbar_init(sb + B_PUB + 8 * s, 4);
    for (int s = 0; s < 14; s++) mbar_init(sb + B_PFULL + 8 * s, 1);
    asm volatile("fence.mbarrier_init.release.cluster;\n" ::: "memory");
    fence_async_smem();
  }
  __syncthreads();

  if (warp >= 8) {
    asm volatile("setmaxnreg.dec.sync.aligned.u32 24;\n");
    if (warp == 8) {
      if (lane == 0) {
        for (int n = 1; n < 30; n++) {
          const uint32_t ph = (n & 1) ^ 1;
          const int c = n == 21 ? 8 : ((j + n - 21) & 7);
          for (int s = 0; s < 6; s++) {
            const uint32_t fb = sb + B_FULL + 8 * s, dst = sb + s * SLOT;
            mbar_wait(sb + B_EMPTY + 8 * s, ph);
            mbar_expect(fb, SLOT);
            if (n == 1) tma2d(dst, &m_qkv, 2 * D_ + 72 * j, 96 * s, fb);
            else if (n < 20) {
              tma2d(dst, &m_w1, 576 * j + 32 * (n - 2), 96 * s, fb);
              tma2d(dst + SLOT / 2, &m_w3, 576 * j + 32 * (n - 2), 96 * s, fb);
            } else if (n == 20) tma2d(dst, &m_qkv, 72 * j, 96 * s, fb);
            else tma2d(dst, &m_w2, 64 * c, 576 * j + 96 * s, fb);
          }
          if (n >= 21) {
            if (n == 21) mbar_wait(sb + B_HFREE, 0);
            mbar_wait(sb + B_EMPTY + 48, n & 1);
            mbar_expect(sb + B_FULL + 48, 80 * 128);
            tma2d(sb + WO_SLOT, &m_wo, 64 * c, 72 * j, sb + B_FULL + 48);
          }
        }
      }
    } else {
      const int ht = tid - 288;
      const uint32_t ep = g_epoch[blockIdx.x] + 1;
      for (int i = ht; i < 36 * 3 * 2; i += 96) {
        const int row = 36 * r + i / 6, g = (i % 6) >> 1;
        prefetch_l2(p.wqkv + (size_t)row * (3 * D_) + g * D_ + 72 * j + (i & 1) * 64);
      }
      mbar_wait(sb + B_XDONE, 0);
      for (int i = ht; i < 3 * 576; i += 96) {
        const int g = i / 576, k = i - g * 576;
        const int col = (g == 2 ? 0 : (g + 1) * D_) + 72 * j + 64;
        asm volatile("cp.async.cg.shared.global [%0], [%1], 16;\n" ::"r"(sb + L24_T + i * 16), "l"(p.wqkv + (size_t)k * (3 * D_) + col) : "memory");
      }
      for (int cb = 0; cb < 9; cb++) {
        if (ht < 72) {
          const __nv_bfloat16* w = ht < 36 ? p.w1 : p.w3;
          const int row = 36 * r + (ht < 36 ? ht : ht - 36);
          prefetch_l2(w + (size_t)row * F_ + 576 * j + cb * 64);
        }
      }
      asm volatile("cp.async.wait_all;\n" ::: "memory");
      fence_async_smem();
      mbar_arrive(sb + B_LFULL);
      for (int i = ht; i < 36 * 9; i += 96) prefetch_l2(p.w2 + (size_t)(576 * j + 36 * r) * D_ + i * 64);
      if (r < 9 && ht < 72) prefetch_l2(p.wo + (size_t)(72 * j + 8 * r) * D_ + ht * 64);

      const int hw = warp - 9;
      mbar_wait(sb + B_KVT, 0);
#pragma unroll 1
      for (int t = ht; t < 360; t += 96) {
        const int hd = t / 10, e2 = t - hd * 10;
        uint32_t ka = sb + PK_T + hd * 4;
        const uint32_t dv = V_T - PK_T + ((hd / 9) * 9 + e2 - hd) * 4;
        float c0 = 0.f, c1 = 0.f, c2 = 0.f, c3 = 0.f;
#pragma unroll 1
        for (int s2 = 0; s2 < 64; s2++) {
          uint32_t k0 = lds32(ka), k1 = lds32(ka + 144), v0 = lds32(ka + dv), v1 = lds32(ka + dv + 144);
          if (e2 == 9) { v0 = 0x3F803F80u; v1 = 0x3F803F80u; }
          c0 = fmaf(blo(k0), blo(v0), c0); c1 = fmaf(bhi(k0), blo(v0), c1); c2 = fmaf(blo(k0), bhi(v0), c2); c3 = fmaf(bhi(k0), bhi(v0), c3);
          c0 = fmaf(blo(k1), blo(v1), c0); c1 = fmaf(bhi(k1), blo(v1), c1); c2 = fmaf(blo(k1), bhi(v1), c2); c3 = fmaf(bhi(k1), bhi(v1), c3);
          ka += 288;
        }
        g_kvp[(j * 16 + r) * 360 + t] = make_float4(c0, c1, c2, c3);
      }
      __syncwarp();
      if (lane == 0) mbar_arrive(sb + B_KVFREE);
      bar_sync(3, 96);
      if (ht == 0) { red_rel(&g_cnt1[j * 32]); wait_ge(&g_cnt1[j * 32], 16 * ep); }
      bar_sync(3, 96);
      if (r < 15) {
        const float* src = reinterpret_cast<const float*>(g_kvp) + j * 16 * 1440 + r * 96 + ht;
        float s = 0.f;
#pragma unroll 8
        for (int rr = 0; rr < 16; rr++) s += __ldcg(src + rr * 1440);
        g_kvs[j * 1440 + r * 96 + ht] = s;
      }
      bar_sync(3, 96);
      if (ht == 0) { red_rel(&g_cnt2[j * 32]); wait_ge(&g_cnt2[j * 32], 16 * ep); }
      bar_sync(3, 96);
      {
        const int g = lane >> 2, q = lane & 3;
#pragma unroll 1
        for (int f = hw; f < 27; f += 3) {
          int t = 0, fb = 0;
          while (f >= fb + o_nk(t)) { fb += o_nk(t); t++; }
          const int ks = o_k0(t) + f - fb;
          const int he = t < 9 ? (8 * t + g) / 18 : (t - 9) * 2 + (g & 1);
          const int el = t < 9 ? 8 * t + g - 18 * he : 18;
          uint32_t b[2];
#pragma unroll
          for (int z = 0; z < 2; z++) {
            const int d = 16 * ks + 8 * z + 2 * q;
            b[z] = 0;
            if (d < 72 && d / 18 == he) {
              const float2 v = __ldcg(reinterpret_cast<const float2*>(g_kvs + j * 1440) + d * 10 + el);
              b[z] = pack2(v.x, v.y);
            }
          }
          sts64(sb + KVF + f * 256 + lane * 8, b[0], b[1]);
        }
        __syncwarp();
        if (lane == 0) mbar_arrive(sb + B_KVRDY);
      }
      if (hw < 2) {
        if (lane == 0) {
          for (int s = 0; s < 8; s++) {
            const int c = s == 0 ? 8 : ((j + s) & 7);
            mbar_wait(sb + B_PUB + 16 * s + 8 * hw, 0);
            st_rel(&g_flag[((r * 9 + c) * 8 + j) * 2 + hw], ep);
          }
        }
      } else {
        if (lane < 8) wait_ge(&g_flag[((r * 9 + 8) * 8 + lane) * 2 + (j >> 2)], ep);
        __syncwarp();
        {
          const uint32_t* src = reinterpret_cast<const uint32_t*>(g_part + (size_t)(((r * 9 + 8) * 8) * 2 + (j >> 2)) * 512 + (j & 3) * 128) + lane;
          const int off0 = ((r * 128 + j * 16 + (lane >> 4) + 8 * (lane & 1)) * D_ + 512 + 8 * ((lane >> 1) & 1) + 2 * ((lane >> 2) & 3)) >> 1;
#pragma unroll 1
          for (int k = 0; k < 16; k++) {
            const int off = off0 + (k & 3) * D_ + (k >> 2) * 8;
            const uint32_t xv = __ldg(reinterpret_cast<const uint32_t*>(p.x) + off);
            uint32_t v[8];
#pragma unroll
            for (int jj = 0; jj < 8; jj++) v[jj] = __ldcg(src + k * 32 + jj * 4096);
            float s0 = blo(xv), s1 = bhi(xv);
#pragma unroll
            for (int jj = 0; jj < 8; jj++) { s0 += blo(v[jj]); s1 += bhi(v[jj]); }
            reinterpret_cast<uint32_t*>(p.out)[off] = pack2(s0, s1);
          }
        }
        mbar_wait(sb + B_HFREE, 0);
        if (lane < 2) {
          for (int s = 1; s < 8; s++) {
            const int src = (j - s) & 7;
            const int idx = ((r * 9 + j) * 8 + src) * 2 + lane;
            uint32_t n = 0;
            while (ld_acq(&g_flag[idx]) != ep) { if (++n > SPIN_LIMIT) __trap(); }
            asm volatile("fence.proxy.async;\n" ::: "memory");
            const uint32_t fb = sb + B_PFULL + 16 * (s - 1) + 8 * lane;
            mbar_expect(fb, 8192);
            bulk_g2s(sb + (lane ? PS1 : PS0) + (s - 1) * 8192, g_part + (size_t)idx * 512, 8192, fb);
          }
        }
        if (lane == 0) g_epoch[blockIdx.x] = ep;
      }
    }
  } else {
    asm volatile("setmaxnreg.inc.sync.aligned.u32 240;\n");
    const int wg = warp >> 2;
    uint32_t a[36][4];
    float dA[32], dB[32];
    const bool l0 = lane == 0;
    constexpr uint64_t dsw128 = mkdesc(sb, 16, 1024, 1);
    constexpr uint64_t dsw64 = mkdesc(sb, SLOT / 2, 512, 2);

    auto stage = [&](float (&d)[32], const uint64_t dbase, const int kstride, const int s, const uint32_t ph, const int rel) {
      mbar_wait(sb + B_FULL + 8 * s, ph);
      wg_fence();
#pragma unroll
      for (int ks = 0; ks < 6; ks++) wgmma_rs64(d, a[s * 6 + ks], dbase + ((s * SLOT + ks * kstride) >> 4), (s | ks) != 0);
      wg_commit();
      wg_wait<1>();
      if (rel >= 0 && l0) mbar_arrive(sb + B_EMPTY + 8 * rel);
    };

    mbar_wait(sb + B_X + 8 * warp, 0);
    uint32_t mb0, mb1;
    float dm0, dm1;
    {
      const uint32_t xa = sb + HB + (warp * 16 + (lane & 15)) * XPITCH + (lane >> 4) * 16;
      float c[4][4];
#pragma unroll
      for (int i = 0; i < 4; i++) { c[i][0] = c[i][1] = c[i][2] = c[i][3] = 0.f; }
#pragma unroll
      for (int ks = 0; ks < 36; ks++) ldsm4(a[ks][0], a[ks][1], a[ks][2], a[ks][3], xa + ks * 32);
      __syncwarp();
      if (l0) mbar_arrive(sb + B_XDONE);
#pragma unroll
      for (int ks = 0; ks < 36; ks++) mma16816(c[ks & 3], a[ks][0], a[ks][1], a[ks][2], a[ks][3], 0x3F803F80u, 0x3F803F80u);
      const float m0 = ((c[0][0] + c[1][0]) + (c[2][0] + c[3][0])) * (1.f / 576.f);
      const float m1 = ((c[0][2] + c[1][2]) + (c[2][2] + c[3][2])) * (1.f / 576.f);
      mb0 = pack2(m0, m0);
      mb1 = pack2(m1, m1);
      dm0 = m0 - blo(mb0);
      dm1 = m1 - blo(mb1);
    }
    float ss0 = 0.f, ss1 = 0.f;
#pragma unroll
    for (int s = 0; s < 6; s++) {
#pragma unroll
      for (int ks = 6 * s; ks < 6 * s + 6; ks++) {
        a[ks][0] = bsub2(a[ks][0], mb0); a[ks][1] = bsub2(a[ks][1], mb1);
        a[ks][2] = bsub2(a[ks][2], mb0); a[ks][3] = bsub2(a[ks][3], mb1);
        float t;
        t = blo(a[ks][0]); ss0 = fmaf(t, t, ss0); t = bhi(a[ks][0]); ss0 = fmaf(t, t, ss0);
        t = blo(a[ks][1]); ss1 = fmaf(t, t, ss1); t = bhi(a[ks][1]); ss1 = fmaf(t, t, ss1);
        t = blo(a[ks][2]); ss0 = fmaf(t, t, ss0); t = bhi(a[ks][2]); ss0 = fmaf(t, t, ss0);
        t = blo(a[ks][3]); ss1 = fmaf(t, t, ss1); t = bhi(a[ks][3]); ss1 = fmaf(t, t, ss1);
      }
      asm volatile("" : "+f"(ss0), "+f"(ss1)::"memory");
      stage(dA, dsw128, 2048, s, 0, s - 1);
    }
    ss0 += __shfl_xor_sync(0xffffffffu, ss0, 1); ss1 += __shfl_xor_sync(0xffffffffu, ss1, 1);
    ss0 += __shfl_xor_sync(0xffffffffu, ss0, 2); ss1 += __shfl_xor_sync(0xffffffffu, ss1, 2);
    const float r0 = rcp(rbf(sqrta(rbf(rbf(fmaxf(ss0 * (1.f / 576.f) - dm0 * dm0, 0.f)) + 1e-5f))));
    const float r1 = rcp(rbf(sqrta(rbf(rbf(fmaxf(ss1 * (1.f / 576.f) - dm1 * dm1, 0.f)) + 1e-5f))));

    const uint32_t tile_off = (warp * 16 + (lane & 15)) * 144 + (lane >> 4) * 16;
    stage(dB, dsw128, 2048, 0, 1, 5);
    pin(dA);
    mbar_wait(sb + B_XDONE, 0);
#pragma unroll
    for (int t = 0; t < 8; t += 2)
      stsm4(sb + PK_T + tile_off + t * 16, pack2(phi(dA[4 * t] * r0), phi(dA[4 * t + 1] * r0)), pack2(phi(dA[4 * t + 2] * r1), phi(dA[4 * t + 3] * r1)),
            pack2(phi(dA[4 * t + 4] * r0), phi(dA[4 * t + 5] * r0)), pack2(phi(dA[4 * t + 6] * r1), phi(dA[4 * t + 7] * r1)));
#pragma unroll
    for (int s = 1; s < 6; s++) stage(dB, dsw128, 2048, s, 1, s - 1);
    {
      float dL[12];
      constexpr uint64_t dl = mkdesc(sb + L24_T, 128, 576 * 16, 0);
      mbar_wait(sb + B_LFULL, 0);
      wg_fence();
#pragma unroll
      for (int ks = 0; ks < 6; ks++) wgmma_rs24(dL, a[ks], dl + ks * 16, ks != 0);
      wg_commit();
      wg_wait<1>();
      if (l0) mbar_arrive(sb + B_EMPTY + 8 * 5);
      wg_fence();
#pragma unroll
      for (int ks = 6; ks < 36; ks++) wgmma_rs24(dL, a[ks], dl + ks * 16, 1);
      wg_commit();
      pin(dB);
#pragma unroll
      for (int t = 0; t < 8; t += 2)
        stsm4(sb + V_T + tile_off + t * 16, pack2(dB[4 * t] * r0, dB[4 * t + 1] * r0), pack2(dB[4 * t + 2] * r1, dB[4 * t + 3] * r1),
              pack2(dB[4 * t + 4] * r0, dB[4 * t + 5] * r0), pack2(dB[4 * t + 6] * r1, dB[4 * t + 7] * r1));
      stage(dB, dsw64, 1024, 0, 0, -1);
      pin(dL);
      const uint32_t lo = (warp * 16 + (lane >> 2)) * 144 + 128 + (lane & 3) * 4;
      sts32(sb + PK_T + lo, pack2(phi(dL[0] * r0), phi(dL[1] * r0)));
      sts32(sb + PK_T + lo + 8 * 144, pack2(phi(dL[2] * r1), phi(dL[3] * r1)));
      sts32(sb + V_T + lo, pack2(dL[4] * r0, dL[5] * r0));
      sts32(sb + V_T + lo + 8 * 144, pack2(dL[6] * r1, dL[7] * r1));
      sts64(sb + Q8 + tid * 8, pack2(phi(dL[8] * r0), phi(dL[9] * r0)), pack2(phi(dL[10] * r1), phi(dL[11] * r1)));
      __syncwarp();
      if (l0) mbar_arrive(sb + B_KVT);
    }
    uint32_t hs = sb + HB + wg * HHALF + (tid & 127) * 16;
    auto epiF = [&](float (&d)[32]) {
      pin(d);
      const float e0 = r0 * -1.4426950408889634f, e1 = r1 * -1.4426950408889634f, q0 = r0 * r0, q1 = r1 * r1;
      uint32_t h[8];
#pragma unroll
      for (int i = 0; i < 8; i++) {
        const float e = (i & 1) ? e1 : e0, q = (i & 1) ? q1 : q0;
        const float g0 = d[2 * i], g1 = d[2 * i + 1];
        h[i] = pack2(g0 * d[2 * i + 16] * q * rcp(1.f + ex2(g0 * e)), g1 * d[2 * i + 17] * q * rcp(1.f + ex2(g1 * e)));
      }
      sts128(hs, h[0], h[1], h[2], h[3]);
      sts128(hs + 2048, h[4], h[5], h[6], h[7]);
      hs += 4096;
    };
#pragma unroll 1
    for (int it = 0; it < 8; it++) {
#pragma unroll
      for (int s = 1; s < 6; s++) stage(dB, dsw64, 1024, s, 0, s - 1);
      stage(dA, dsw64, 1024, 0, 1, 5);
      if (it == 4) mbar_wait(sb + B_KVFREE, 0);
      epiF(dB);
#pragma unroll
      for (int s = 1; s < 6; s++) stage(dA, dsw64, 1024, s, 1, s - 1);
      stage(dB, dsw64, 1024, 0, 0, 5);
      epiF(dA);
    }
#pragma unroll
    for (int s = 1; s < 6; s++) stage(dB, dsw64, 1024, s, 0, s - 1);
    stage(dA, dsw64, 1024, 0, 1, 5);
    epiF(dB);
#pragma unroll
    for (int s = 1; s < 6; s++) stage(dA, dsw64, 1024, s, 1, s - 1);
    stage(dB, dsw128, 2048, 0, 0, 5);
    epiF(dA);
    hs -= 18 * 4096;
#pragma unroll
    for (int s = 1; s < 6; s++) {
      stage(dB, dsw128, 2048, s, 0, s - 1);
#pragma unroll
      for (int ks = 6 * s - 6; ks < 6 * s; ks++) lds128(a[ks][0], a[ks][1], a[ks][2], a[ks][3], hs + ks * 2048);
    }
    const uint32_t ot = sb + (wg ? OT1 : OT0);
    const uint64_t do_a = mkdesc(ot, 128, 1280, 0);
    constexpr uint64_t do_b = mkdesc(sb + WO_SLOT, 16, 1024, 1);
    auto stageO = [&](float (&d)[32], const uint32_t ph) {
      mbar_wait(sb + B_FULL + 48, ph);
      wg_fence();
#pragma unroll
      for (int ks = 0; ks < 5; ks++) wgmma_ss64(d, do_a + ks * 16, do_b + ks * 128);
      wg_commit();
      wg_wait<1>();
      if (l0) mbar_arrive(sb + B_EMPTY + 8 * 5);
    };
    auto epiP = [&](float (&d)[32], const int step) {
      pin(d);
      const int c = step == 0 ? 8 : ((j + step) & 7);
      uint4* dst = g_part + (size_t)(((r * 9 + c) * 8 + j) * 2 + wg) * 512 + (warp & 3) * 128 + lane;
#pragma unroll
      for (int i = 0; i < 4; i++)
        __stcg(dst + i * 32, make_uint4(pack2(d[8 * i], d[8 * i + 1]), pack2(d[8 * i + 2], d[8 * i + 3]), pack2(d[8 * i + 4], d[8 * i + 5]), pack2(d[8 * i + 6], d[8 * i + 7])));
      __syncwarp();
      if (l0) mbar_arrive(sb + B_PUB + 16 * step + 8 * wg);
    };
    stage(dA, dsw128, 2048, 0, 1, 5);
#pragma unroll
    for (int ks = 30; ks < 36; ks++) lds128(a[ks][0], a[ks][1], a[ks][2], a[ks][3], hs + ks * 2048);
    {
      pin(dB);
      uint32_t pq[18];
#pragma unroll
      for (int i = 0; i < 16; i++) {
        const float rr = (i & 1) ? r1 : r0;
        pq[i] = pack2(phi(dB[2 * i] * rr), phi(dB[2 * i + 1] * rr));
      }
      lds64(pq[16], pq[17], sb + Q8 + tid * 8);
      fence_async_smem();
      __syncwarp();
      if (l0) mbar_arrive(sb + B_HFREE);
      stage(dA, dsw128, 2048, 1, 1, 0);
      mbar_wait(sb + B_KVRDY, 0);
      bar_sync(1 + wg, 128);
      const uint32_t fa = sb + KVF + lane * 8;
      auto omma = [&](float (&c)[4], const int t) {
        c[0] = c[1] = c[2] = c[3] = 0.f;
#pragma unroll
        for (int z = 0; z < o_nk(t); z++) {
          const int ks = o_k0(t) + z;
          uint32_t b0, b1;
          lds64(b0, b1, fa + (o_base(t) + z) * 256);
          if (ks < 4) mma16816(c, pq[4 * ks], pq[4 * ks + 1], pq[4 * ks + 2], pq[4 * ks + 3], b0, b1);
          else mma16816(c, pq[16], pq[17], 0u, 0u, b0, b1);
        }
      };
      float iv[4][2];
      {
        float cx[4], cy[4];
        omma(cx, 9);
        omma(cy, 10);
        iv[0][0] = rcp(cx[0] + 1e-6f); iv[1][0] = rcp(cx[1] + 1e-6f); iv[0][1] = rcp(cx[2] + 1e-6f); iv[1][1] = rcp(cx[3] + 1e-6f);
        iv[2][0] = rcp(cy[0] + 1e-6f); iv[3][0] = rcp(cy[1] + 1e-6f); iv[2][1] = rcp(cy[2] + 1e-6f); iv[3][1] = rcp(cy[3] + 1e-6f);
      }
      const int q = lane & 3;
      const uint32_t oa = ot + ((warp & 3) * 2 + ((lane >> 3) & 1)) * 1280 + (lane >> 4) * 128 + (lane & 7) * 16;
#pragma unroll
      for (int t = 0; t < 10; t += 2) {
        uint32_t o[4];
#pragma unroll
        for (int z = 0; z < 2; z++) {
          const int tt = t + z;
          if (tt < 9) {
            float c[4];
            omma(c, tt);
            const int hl = (8 * tt) / 18, hh = (8 * tt + 7) / 18;
            const bool up = hl != hh && 8 * tt + 2 * q >= 18 * hh;
            const float i0 = up ? iv[hh][0] : iv[hl][0], i1 = up ? iv[hh][1] : iv[hl][1];
            o[2 * z] = pack2(c[0] * i0, c[1] * i0);
            o[2 * z + 1] = pack2(c[2] * i1, c[3] * i1);
          } else {
            o[2 * z] = 0; o[2 * z + 1] = 0;
          }
        }
        stsm4(oa + t * 128, o[0], o[1], o[2], o[3]);
        if (t == 2) stage(dA, dsw128, 2048, 2, 1, 1);
      }
      fence_async_smem();
    }
#pragma unroll
    for (int s = 3; s < 6; s++) stage(dA, dsw128, 2048, s, 1, s - 1);
    bar_sync(1 + wg, 128);
    stageO(dA, 0);
    stage(dB, dsw128, 2048, 0, 0, 6);
    epiP(dA, 0);
#pragma unroll 1
    for (int it = 0; it < 3; it++) {
#pragma unroll
      for (int s = 1; s < 6; s++) stage(dB, dsw128, 2048, s, 0, s - 1);
      stageO(dB, 1);
      stage(dA, dsw128, 2048, 0, 1, 6);
      epiP(dB, 1 + 2 * it);
#pragma unroll
      for (int s = 1; s < 6; s++) stage(dA, dsw128, 2048, s, 1, s - 1);
      stageO(dA, 0);
      stage(dB, dsw128, 2048, 0, 0, 6);
      epiP(dA, 2 + 2 * it);
    }
#pragma unroll
    for (int s = 1; s < 6; s++) stage(dB, dsw128, 2048, s, 0, s - 1);
    stageO(dB, 1);
    stage(dA, dsw128, 2048, 0, 1, 6);
    epiP(dB, 7);
    {
      const __nv_bfloat16* xp = p.x + (size_t)(r * 128 + warp * 16 + (lane >> 2)) * D_ + 64 * j + 2 * (lane & 3);
      uint32_t xv[16];
#pragma unroll
      for (int t = 0; t < 8; t++) {
        xv[2 * t] = __ldg(reinterpret_cast<const uint32_t*>(xp + 8 * t));
        xv[2 * t + 1] = __ldg(reinterpret_cast<const uint32_t*>(xp + 8 * D_ + 8 * t));
      }
      stage(dA, dsw128, 2048, 1, 1, -1);
#pragma unroll
      for (int i = 0; i < 16; i++) { dB[2 * i] = blo(xv[i]); dB[2 * i + 1] = bhi(xv[i]); }
    }
    const uint32_t ps = sb + (wg ? PS1 : PS0) + (warp & 3) * 2048;
    auto addp = [&](const int s) {
      mbar_wait(sb + B_PFULL + 16 * s + 8 * wg, 0);
#pragma unroll
      for (int i = 0; i < 4; i++) {
        uint32_t v0, v1, v2, v3;
        lds128(v0, v1, v2, v3, ps + s * 8192 + i * 512 + lane * 16);
        dB[8 * i] += blo(v0); dB[8 * i + 1] += bhi(v0); dB[8 * i + 2] += blo(v1); dB[8 * i + 3] += bhi(v1);
        dB[8 * i + 4] += blo(v2); dB[8 * i + 5] += bhi(v2); dB[8 * i + 6] += blo(v3); dB[8 * i + 7] += bhi(v3);
      }
      pin(dB);
    };
    addp(0);
    stage(dA, dsw128, 2048, 2, 1, -1);
    addp(1); addp(2);
    stage(dA, dsw128, 2048, 3, 1, -1);
    addp(3);
    stage(dA, dsw128, 2048, 4, 1, -1);
    addp(4);
    stage(dA, dsw128, 2048, 5, 1, -1);
    addp(5);
    stageO(dA, 0);
    addp(6);
    wg_wait<0>();
    pin(dA);
    {
      __syncwarp();
      const int row = lane & 15;
#pragma unroll
      for (int t = 0; t < 8; t += 2)
        stsm4(ps + row * 128 + (((t + (lane >> 4)) ^ (row & 7)) << 4),
              pack2(dA[4 * t] + dB[4 * t], dA[4 * t + 1] + dB[4 * t + 1]), pack2(dA[4 * t + 2] + dB[4 * t + 2], dA[4 * t + 3] + dB[4 * t + 3]),
              pack2(dA[4 * t + 4] + dB[4 * t + 4], dA[4 * t + 5] + dB[4 * t + 5]), pack2(dA[4 * t + 6] + dB[4 * t + 6], dA[4 * t + 7] + dB[4 * t + 7]));
      __syncwarp();
#pragma unroll
      for (int i = 0; i < 4; i++) {
        const int rr = i * 4 + (lane >> 3), ch = lane & 7;
        uint4 v;
        lds128(v.x, v.y, v.z, v.w, ps + rr * 128 + ((ch ^ (rr & 7)) << 4));
        *reinterpret_cast<uint4*>(p.out + (size_t)(r * 128 + warp * 16 + rr) * D_ + 64 * j + ch * 8) = v;
      }
    }
  }
}

typedef CUresult (*EncodeFn)(CUtensorMap*, CUtensorMapDataType, cuuint32_t, void*, const cuuint64_t*, const cuuint64_t*, const cuuint32_t*,
                             const cuuint32_t*, CUtensorMapInterleave, CUtensorMapSwizzle, CUtensorMapL2promotion, CUtensorMapFloatOOBfill);

CUtensorMap make_map(EncodeFn enc, const void* ptr, int rows, int cols, int brow, int bcol, CUtensorMapSwizzle sw) {
  CUtensorMap m;
  cuuint64_t gd[2] = {(cuuint64_t)cols, (cuuint64_t)rows};
  cuuint64_t gs[1] = {(cuuint64_t)cols * 2};
  cuuint32_t bd[2] = {(cuuint32_t)bcol, (cuuint32_t)brow};
  cuuint32_t es[2] = {1, 1};
  enc(&m, CU_TENSOR_MAP_DATA_TYPE_BFLOAT16, 2, const_cast<void*>(ptr), gd, gs, bd, es, CU_TENSOR_MAP_INTERLEAVE_NONE, sw,
      CU_TENSOR_MAP_L2_PROMOTION_L2_128B, CU_TENSOR_MAP_FLOAT_OOB_FILL_NONE);
  return m;
}

}

extern "C" void kernel_launch(void* const* d_in, const int* in_sizes, int n_in, void* d_out, int out_size) {
  (void)in_sizes; (void)n_in; (void)out_size;
  static EncodeFn enc = nullptr;
  if (!enc) {
    cudaDriverEntryPointQueryResult qr;
    cudaGetDriverEntryPoint("cuTensorMapEncodeTiled", (void**)&enc, cudaEnableDefault, &qr);
    cudaFuncSetAttribute(fused_block_kernel, cudaFuncAttributeMaxDynamicSharedMemorySize, SMEM_BYTES);
  }
  Params p;
  p.x = (const __nv_bfloat16*)d_in[0];
  p.wqkv = (const __nv_bfloat16*)d_in[1];
  p.wo = (const __nv_bfloat16*)d_in[2];
  p.w1 = (const __nv_bfloat16*)d_in[4];
  p.w3 = (const __nv_bfloat16*)d_in[5];
  p.w2 = (const __nv_bfloat16*)d_in[6];
  p.out = (__nv_bfloat16*)d_out;
  const CUtensorMap m_qkv = make_map(enc, p.wqkv, D_, 3 * D_, 96, 64, CU_TENSOR_MAP_SWIZZLE_128B);
  const CUtensorMap m_w1 = make_map(enc, p.w1, D_, F_, 96, 32, CU_TENSOR_MAP_SWIZZLE_64B);
  const CUtensorMap m_w3 = make_map(enc, p.w3, D_, F_, 96, 32, CU_TENSOR_MAP_SWIZZLE_64B);
  const CUtensorMap m_w2 = make_map(enc, p.w2, F_, D_, 96, 64, CU_TENSOR_MAP_SWIZZLE_128B);
  const CUtensorMap m_wo = make_map(enc, p.wo, D_, D_, 80, 64, CU_TENSOR_MAP_SWIZZLE_128B);
  fused_block_kernel<<<128, NTHREADS, SMEM_BYTES>>>(m_qkv, m_w1, m_w3, m_w2, m_wo, p);
}
```

```cpp
#include <cuda_runtime.h>
#include <cuda.h>
#include <cuda_bf16.h>
#include <stdint.h>

namespace {

constexpr int D_ = 576, F_ = 4608;
constexpr int NTHREADS = 384;

constexpr uint32_t SLOT = 12288;
constexpr uint32_t HB = 6 * SLOT;
constexpr uint32_t HHALF = 73728;
constexpr uint32_t PK_T = HB + 55296;
constexpr uint32_t V_T = HB + HHALF + 55296;
constexpr uint32_t L24_T = HB + 16384;
constexpr uint32_t WO_SLOT = HB + 67584;
constexpr uint32_t OT0 = HB, OT1 = HB + 137216;
constexpr uint32_t PS0 = HB + 10240, PS1 = HB + 79872;
constexpr uint32_t Q8 = HB + 2 * HHALF;
constexpr uint32_t WOB = Q8 + 2048;
constexpr uint32_t KVS = WOB + 5184;
constexpr uint32_t ZS = KVS + 1440;
constexpr uint32_t BARS = ZS + 288;
constexpr uint32_t SMEM_BYTES = BARS + 512;

constexpr uint32_t B_FULL = BARS;
constexpr uint32_t B_EMPTY = BARS + 56;
constexpr uint32_t B_X = BARS + 112;
constexpr uint32_t B_XDONE = BARS + 184;
constexpr uint32_t B_LFULL = BARS + 192;
constexpr uint32_t B_KVT = BARS + 200;
constexpr uint32_t B_KVFREE = BARS + 208;
constexpr uint32_t B_MRDY = BARS + 216;
constexpr uint32_t B_HFREE = BARS + 224;
constexpr uint32_t B_PUB = BARS + 232;
constexpr uint32_t B_PFULL = BARS + 360;

constexpr uint32_t SPIN_LIMIT = 1u << 22;

__device__ uint4 g_part[16 * 9 * 8 * 2 * 512];
__device__ float4 g_kvp[8 * 16 * 360];
__device__ __align__(128) __nv_bfloat16 g_M[8 * 80 * 576];
__device__ float g_z[8 * 72];
__device__ uint32_t g_cnt1[8 * 32], g_cnt2[8 * 32];
__device__ uint32_t g_flag[16 * 9 * 8 * 2];
__device__ uint32_t g_epoch[128];

#define TS(slot, i)
#define TSC(i)
#define GT(i)

__device__ __forceinline__ void wg_fence() { asm volatile("wgmma.fence.sync.aligned;\n" ::: "memory"); }
__device__ __forceinline__ void wg_commit() { asm volatile("wgmma.commit_group.sync.aligned;\n" ::: "memory"); }
template <int N> __device__ __forceinline__ void wg_wait() { asm volatile("wgmma.wait_group.sync.aligned %0;\n" ::"n"(N) : "memory"); }
__host__ __device__ constexpr uint64_t mkdesc(uint32_t addr, uint32_t lbo, uint32_t sbo, uint32_t sw) {
  return (uint64_t)((addr & 0x3FFFF) >> 4) | ((uint64_t)(lbo >> 4) << 16) | ((uint64_t)(sbo >> 4) << 32) | ((uint64_t)sw << 62);
}
__device__ __forceinline__ void mbar_init(uint32_t a, uint32_t c) { asm volatile("mbarrier.init.shared::cta.b64 [%0], %1;\n" ::"r"(a), "r"(c) : "memory"); }
__device__ __forceinline__ void mbar_expect(uint32_t a, uint32_t b) { asm volatile("mbarrier.arrive.expect_tx.shared::cta.b64 _, [%0], %1;\n" ::"r"(a), "r"(b) : "memory"); }
__device__ __forceinline__ void mbar_arrive(uint32_t a) { asm volatile("mbarrier.arrive.shared::cta.b64 _, [%0];\n" ::"r"(a) : "memory"); }
__device__ __forceinline__ void mbar_wait(uint32_t a, uint32_t ph) {
  asm volatile(
      "{\n.reg .pred p;\n.reg .u32 n;\n"
      "mbarrier.try_wait.parity.shared::cta.b64 p, [%0], %1;\n"
      "@p bra DONE;\n"
      "mov.u32 n, 0;\n"
      "LOOP:\n"
      "mbarrier.try_wait.parity.shared::cta.b64 p, [%0], %1;\n"
      "@p bra DONE;\n"
      "add.u32 n, n, 1;\n"
      "setp.lt.u32 p, n, %2;\n"
      "@p bra LOOP;\n"
      "trap;\n"
      "DONE:\n}\n" ::"r"(a), "r"(ph), "n"(SPIN_LIMIT) : "memory");
}
__device__ __forceinline__ bool mbar_test(uint32_t a, uint32_t ph) {
  uint32_t ok;
  asm volatile("{\n.reg .pred p;\nmbarrier.try_wait.parity.shared::cta.b64 p, [%1], %2, 200;\nselp.u32 %0, 1, 0, p;\n}\n" : "=r"(ok) : "r"(a), "r"(ph) : "memory");
  return ok;
}
__device__ __forceinline__ void cp_async16(uint32_t dst, const void* src) {
  asm volatile("cp.async.cg.shared.global [%0], [%1], 16;\n" ::"r"(dst), "l"(src) : "memory");
}
__device__ __forceinline__ void tma2d(uint32_t dst, const CUtensorMap* m, int c0, int c1, uint32_t bar) {
  asm volatile("cp.async.bulk.tensor.2d.shared::cluster.global.mbarrier::complete_tx::bytes [%0], [%1, {%3, %4}], [%2];\n" ::"r"(dst), "l"(m), "r"(bar), "r"(c0), "r"(c1) : "memory");
}
__device__ __forceinline__ void bulk_g2s(uint32_t dst, const void* src, uint32_t bytes, uint32_t bar) {
  asm volatile("cp.async.bulk.shared::cluster.global.mbarrier::complete_tx::bytes [%0], [%1], %2, [%3];\n" ::"r"(dst), "l"(src), "r"(bytes), "r"(bar) : "memory");
}
__device__ __forceinline__ void prefetch_l2(const void* p) { asm volatile("prefetch.global.L2 [%0];\n" ::"l"(p)); }
__device__ __forceinline__ void fence_async_smem() { asm volatile("fence.proxy.async.shared::cta;\n" ::: "memory"); }
__device__ __forceinline__ void bar_sync(int id, int n) { asm volatile("bar.sync %0, %1;\n" ::"r"(id), "r"(n) : "memory"); }
__device__ __forceinline__ void ldsm4(uint32_t& r0, uint32_t& r1, uint32_t& r2, uint32_t& r3, uint32_t a) {
  asm volatile("ldmatrix.sync.aligned.m8n8.x4.shared.b16 {%0,%1,%2,%3}, [%4];\n" : "=r"(r0), "=r"(r1), "=r"(r2), "=r"(r3) : "r"(a) : "memory");
}
__device__ __forceinline__ void stsm4(uint32_t a, uint32_t r0, uint32_t r1, uint32_t r2, uint32_t r3) {
  asm volatile("stmatrix.sync.aligned.m8n8.x4.shared.b16 [%0], {%1,%2,%3,%4};\n" ::"r"(a), "r"(r0), "r"(r1), "r"(r2), "r"(r3) : "memory");
}
__device__ __forceinline__ void sts128(uint32_t a, uint32_t r0, uint32_t r1, uint32_t r2, uint32_t r3) {
  asm volatile("st.shared.v4.b32 [%0], {%1,%2,%3,%4};\n" ::"r"(a), "r"(r0), "r"(r1), "r"(r2), "r"(r3) : "memory");
}
__device__ __forceinline__ void lds128(uint32_t& r0, uint32_t& r1, uint32_t& r2, uint32_t& r3, uint32_t a) {
  asm volatile("ld.shared.v4.b32 {%0,%1,%2,%3}, [%4];\n" : "=r"(r0), "=r"(r1), "=r"(r2), "=r"(r3) : "r"(a) : "memory");
}
__device__ __forceinline__ void sts64(uint32_t a, uint32_t r0, uint32_t r1) { asm volatile("st.shared.v2.b32 [%0], {%1,%2};\n" ::"r"(a), "r"(r0), "r"(r1) : "memory"); }
__device__ __forceinline__ void lds64(uint32_t& r0, uint32_t& r1, uint32_t a) { asm volatile("ld.shared.v2.b32 {%0,%1}, [%2];\n" : "=r"(r0), "=r"(r1) : "r"(a) : "memory"); }
__device__ __forceinline__ uint32_t lds32(uint32_t a) { uint32_t v; asm volatile("ld.shared.b32 %0, [%1];\n" : "=r"(v) : "r"(a) : "memory"); return v; }
__device__ __forceinline__ void sts32(uint32_t a, uint32_t r0) { asm volatile("st.shared.b32 [%0], %1;\n" ::"r"(a), "r"(r0) : "memory"); }
__device__ __forceinline__ void mma16816(float (&c)[4], uint32_t a0, uint32_t a1, uint32_t a2, uint32_t a3, uint32_t b0, uint32_t b1) {
  asm volatile("mma.sync.aligned.m16n8k16.row.col.f32.bf16.bf16.f32 {%0,%1,%2,%3}, {%4,%5,%6,%7}, {%8,%9}, {%0,%1,%2,%3};\n"
               : "+f"(c[0]), "+f"(c[1]), "+f"(c[2]), "+f"(c[3]) : "r"(a0), "r"(a1), "r"(a2), "r"(a3), "r"(b0), "r"(b1));
}
__device__ __forceinline__ uint32_t pack2(float lo, float hi) {
  uint32_t r;
  asm("cvt.rn.bf16x2.f32 %0, %1, %2;\n" : "=r"(r) : "f"(hi), "f"(lo));
  return r;
}
__device__ __forceinline__ float blo(uint32_t w) { return __uint_as_float(w << 16); }
__device__ __forceinline__ float bhi(uint32_t w) { return __uint_as_float(w & 0xffff0000u); }
__device__ __forceinline__ float rbf(float x) { return __bfloat162float(__float2bfloat16_rn(x)); }
__device__ __forceinline__ float ex2(float x) { float r; asm("ex2.approx.ftz.f32 %0, %1;\n" : "=f"(r) : "f"(x)); return r; }
__device__ __forceinline__ float rcp(float x) { float r; asm("rcp.approx.ftz.f32 %0, %1;\n" : "=f"(r) : "f"(x)); return r; }
__device__ __forceinline__ float sqrta(float x) { float r; asm("sqrt.approx.ftz.f32 %0, %1;\n" : "=f"(r) : "f"(x)); return r; }
__device__ __forceinline__ uint32_t bsub2(uint32_t a, uint32_t b) { uint32_t r; asm("sub.rn.bf16x2 %0, %1, %2;\n" : "=r"(r) : "r"(a), "r"(b)); return r; }
__device__ __forceinline__ uint32_t ld_acq(const uint32_t* p) { uint32_t v; asm volatile("ld.acquire.gpu.global.u32 %0, [%1];\n" : "=r"(v) : "l"(p) : "memory"); return v; }
__device__ __forceinline__ void st_rel(uint32_t* p, uint32_t v) { asm volatile("st.release.gpu.global.u32 [%0], %1;\n" ::"l"(p), "r"(v) : "memory"); }
__device__ __forceinline__ void red_rel(uint32_t* p) { asm volatile("red.release.gpu.global.add.u32 [%0], 1;\n" ::"l"(p) : "memory"); }
__device__ __forceinline__ void wait_ge(const uint32_t* p, uint32_t target) {
  uint32_t n = 0;
  while ((int32_t)(ld_acq(p) - target) < 0) {
    __nanosleep(64);
    if (++n > SPIN_LIMIT) __trap();
  }
}
__device__ __forceinline__ float phi(float t) { return (t > 0.f ? t + 1.f : ex2(t * 1.4426950408889634f)) + 1e-6f; }

#define ACC8(d, o) "+f"(d[o + 0]), "+f"(d[o + 1]), "+f"(d[o + 2]), "+f"(d[o + 3]), "+f"(d[o + 4]), "+f"(d[o + 5]), "+f"(d[o + 6]), "+f"(d[o + 7])
#define REGS32 "{%0,%1,%2,%3,%4,%5,%6,%7,%8,%9,%10,%11,%12,%13,%14,%15,%16,%17,%18,%19,%20,%21,%22,%23,%24,%25,%26,%27,%28,%29,%30,%31}"
__device__ __forceinline__ void wgmma_rs64(float (&d)[32], const uint32_t (&a)[4], uint64_t db, int acc) {
  asm volatile("{\n.reg .pred p;\nsetp.ne.b32 p, %37, 0;\n"
               "wgmma.mma_async.sync.aligned.m64n64k16.f32.bf16.bf16 " REGS32 ", {%32,%33,%34,%35}, %36, p, 1, 1, 1;\n}\n"
               : ACC8(d, 0), ACC8(d, 8), ACC8(d, 16), ACC8(d, 24)
               : "r"(a[0]), "r"(a[1]), "r"(a[2]), "r"(a[3]), "l"(db), "r"(acc));
}
__device__ __forceinline__ void wgmma_ss64(float (&d)[32], uint64_t da, uint64_t db) {
  asm volatile("wgmma.mma_async.sync.aligned.m64n64k16.f32.bf16.bf16 " REGS32 ", %32, %33, 1, 1, 1, 0, 1;\n"
               : ACC8(d, 0), ACC8(d, 8), ACC8(d, 16), ACC8(d, 24)
               : "l"(da), "l"(db));
}
__device__ __forceinline__ void wgmma_rs24(float (&d)[12], const uint32_t (&a)[4], uint64_t db, int acc) {
  asm volatile("{\n.reg .pred p;\nsetp.ne.b32 p, %17, 0;\n"
               "wgmma.mma_async.sync.aligned.m64n24k16.f32.bf16.bf16 {%0,%1,%2,%3,%4,%5,%6,%7,%8,%9,%10,%11}, {%12,%13,%14,%15}, %16, p, 1, 1, 1;\n}\n"
               : ACC8(d, 0), "+f"(d[8]), "+f"(d[9]), "+f"(d[10]), "+f"(d[11])
               : "r"(a[0]), "r"(a[1]), "r"(a[2]), "r"(a[3]), "l"(db), "r"(acc));
}
template <int N> __device__ __forceinline__ void pin(float (&d)[N]) {
#pragma unroll
  for (int i = 0; i < N; i++) asm volatile("" : "+f"(d[i])::"memory");
}

__device__ __forceinline__ void pin8(float (&d)[32], const int o) { asm volatile("" : ACC8(d, o)::"memory"); }

struct Params {
  const __nv_bfloat16* x;
  const __nv_bfloat16* wqkv;
  const __nv_bfloat16* wo;
  const __nv_bfloat16* w1;
  const __nv_bfloat16* w3;
  const __nv_bfloat16* w2;
  __nv_bfloat16* out;
};

__global__ void __launch_bounds__(NTHREADS, 1)
fused_block_kernel(const __grid_constant__ CUtensorMap m_qkv, const __grid_constant__ CUtensorMap m_w1,
                   const __grid_constant__ CUtensorMap m_w3, const __grid_constant__ CUtensorMap m_w2,
                   const __grid_constant__ CUtensorMap m_M, const __grid_constant__ CUtensorMap m_x, const Params p) {
  extern __shared__ __align__(1024) uint8_t smem_raw[];
  constexpr uint32_t sb = 1024;
  if ((uint32_t)__cvta_generic_to_shared(smem_raw) != sb) __trap();
  const int tid = threadIdx.x, warp = tid >> 5, lane = tid & 31;
  const int r = blockIdx.x >> 3, j = blockIdx.x & 7;

  GT(0); TSC(0);
  const int cmain = 72 * j + 8 * (j & 1);
  if (tid == 256) {
    for (int s = 0; s < 9; s++) mbar_init(sb + B_X + 8 * s, 1);
    asm volatile("fence.mbarrier_init.release.cluster;\n" ::: "memory");
#pragma unroll
    for (int b = 0; b < 9; b++) {
      mbar_expect(sb + B_X + 8 * b, 16384);
      tma2d(sb + HB + b * 16384, &m_x, 64 * b, 128 * r, sb + B_X + 8 * b);
    }
    for (int s = 0; s < 7; s++) { mbar_init(sb + B_FULL + 8 * s, 1); mbar_init(sb + B_EMPTY + 8 * s, 8); }
    asm volatile("fence.mbarrier_init.release.cluster;\n" ::: "memory");
#pragma unroll
    for (int s = 0; s < 6; s++) {
      mbar_expect(sb + B_FULL + 8 * s, SLOT);
      tma2d(sb + s * SLOT, &m_qkv, D_ + cmain, 96 * s, sb + B_FULL + 8 * s);
    }
  } else if (tid == 288) {
    mbar_init(sb + B_XDONE, 8);
    mbar_init(sb + B_LFULL, 96);
    mbar_init(sb + B_KVT, 8);
    mbar_init(sb + B_KVFREE, 3);
    mbar_init(sb + B_MRDY, 3);
    mbar_init(sb + B_HFREE, 8);
    for (int s = 0; s < 16; s++) mbar_init(sb + B_PUB + 8 * s, 4);
    for (int s = 0; s < 14; s++) mbar_init(sb + B_PFULL + 8 * s, 1);
    asm volatile("fence.mbarrier_init.release.cluster;\n" ::: "memory");
  }
  __syncthreads();

  if (warp >= 8) {
    asm volatile("setmaxnreg.dec.sync.aligned.u32 24;\n");
    if (warp == 8) {
      if (lane == 0) {
#pragma unroll
        for (int s = 0; s < 6; s++) {
          mbar_wait(sb + B_EMPTY + 8 * s, 0);
          mbar_expect(sb + B_FULL + 8 * s, SLOT);
          tma2d(sb + s * SLOT, &m_qkv, 2 * D_ + cmain, 96 * s, sb + B_FULL + 8 * s);
        }
#pragma unroll 1
        for (int n = 0; n < 18; n++) {
          const int col = 576 * j + 32 * n;
#pragma unroll
          for (int s = 0; s < 6; s++) {
            mbar_wait(sb + B_EMPTY + 8 * s, (n & 1) ^ 1);
            mbar_expect(sb + B_FULL + 8 * s, SLOT);
            tma2d(sb + s * SLOT, &m_w1, col, 96 * s, sb + B_FULL + 8 * s);
            tma2d(sb + s * SLOT + SLOT / 2, &m_w3, col, 96 * s, sb + B_FULL + 8 * s);
          }
        }
#pragma unroll
        for (int s = 0; s < 6; s++) {
          mbar_wait(sb + B_EMPTY + 8 * s, 1);
          mbar_expect(sb + B_FULL + 8 * s, SLOT);
          tma2d(sb + s * SLOT, &m_qkv, cmain, 96 * s, sb + B_FULL + 8 * s);
        }
#pragma unroll 1
        for (int n = 0; n < 9; n++) {
          const int col = n == 0 ? 512 : 64 * ((j + n) & 7);
#pragma unroll
          for (int s = 0; s < 6; s++) {
            mbar_wait(sb + B_EMPTY + 8 * s, n & 1);
            mbar_expect(sb + B_FULL + 8 * s, SLOT);
            tma2d(sb + s * SLOT, &m_w2, col, 576 * j + 96 * s, sb + B_FULL + 8 * s);
          }
          if (n == 0) {
            mbar_wait(sb + B_HFREE, 0);
            mbar_wait(sb + B_MRDY, 0);
            asm volatile("fence.proxy.async;\n" ::: "memory");
          }
          mbar_wait(sb + B_EMPTY + 48, (n & 1) ^ 1);
          mbar_expect(sb + B_FULL + 48, 80 * 128);
          tma2d(sb + WO_SLOT, &m_M, col, 80 * j, sb + B_FULL + 48);
        }
      }
    } else {
      const int ht = tid - 288;
      const uint32_t ep = g_epoch[blockIdx.x] + 1;
#pragma unroll 1
      for (int i = ht; i < 36 * 3 * 2; i += 96) {
        const int row = 36 * r + i / 6, g = (i % 6) >> 1;
        prefetch_l2(p.wqkv + (size_t)row * (3 * D_) + g * D_ + 72 * j + (i & 1) * 64);
      }
      mbar_wait(sb + B_XDONE, 0);
#pragma unroll 1
      for (int i = ht; i < 3 * 576; i += 96) {
        const int g = i / 576, k = i - g * 576;
        const int col = (g == 2 ? 0 : (g + 1) * D_) + 72 * j + ((j & 1) ? 0 : 64);
        cp_async16(sb + L24_T + i * 16, p.wqkv + (size_t)k * (3 * D_) + col);
      }
#pragma unroll 1
      for (int i = ht; i < 18 * 18; i += 96) {
        const int e = i / 18, c = i - e * 18;
        cp_async16(sb + WOB + i * 16, p.wo + (size_t)(72 * j + 18 * (r >> 2) + e) * D_ + 144 * (r & 3) + c * 8);
      }
      if (ht < 72) {
        const __nv_bfloat16* w = (ht < 36 ? p.w1 : p.w3) + (size_t)(36 * r + (ht < 36 ? ht : ht - 36)) * F_ + 576 * j;
#pragma unroll
        for (int cb = 0; cb < 9; cb++) prefetch_l2(w + cb * 64);
      }
      asm volatile("cp.async.wait_all;\n" ::: "memory");
      fence_async_smem();
      mbar_arrive(sb + B_LFULL);
      if (warp == 9) TS(3, 1);
#pragma unroll 1
      for (int i = ht; i < 36 * 9; i += 96) prefetch_l2(p.w2 + (size_t)(576 * j + 36 * r) * D_ + i * 64);

      mbar_wait(sb + B_KVT, 0);
      if (warp == 9) TS(3, 2);
#pragma unroll 1
      for (int t = ht; t < 360; t += 96) {
        const int hd = t / 10, e2 = t - hd * 10;
        uint32_t ka = sb + PK_T + hd * 4;
        uint32_t va = sb + V_T + ((hd / 9) * 9 + e2) * 4;
        const bool one = e2 == 9;
        float c0 = 0.f, c1 = 0.f, c2 = 0.f, c3 = 0.f;
        uint32_t k0 = lds32(ka), k1 = lds32(ka + 144), v0 = lds32(va), v1 = lds32(va + 144);
#pragma unroll 1
        for (int s2 = 0; s2 < 32; s2++) {
          const uint32_t k2 = lds32(ka + 288), k3 = lds32(ka + 432);
          uint32_t v2 = lds32(va + 288), v3 = lds32(va + 432);
          if (one) { v0 = 0x3F803F80u; v1 = 0x3F803F80u; }
          c0 = fmaf(blo(k0), blo(v0), c0); c1 = fmaf(bhi(k0), blo(v0), c1); c2 = fmaf(blo(k0), bhi(v0), c2); c3 = fmaf(bhi(k0), bhi(v0), c3);
          c0 = fmaf(blo(k1), blo(v1), c0); c1 = fmaf(bhi(k1), blo(v1), c1); c2 = fmaf(blo(k1), bhi(v1), c2); c3 = fmaf(bhi(k1), bhi(v1), c3);
          ka += 576; va += 576;
          k0 = lds32(ka); k1 = lds32(ka + 144); v0 = lds32(va); v1 = lds32(va + 144);
          if (one) { v2 = 0x3F803F80u; v3 = 0x3F803F80u; }
          c0 = fmaf(blo(k2), blo(v2), c0); c1 = fmaf(bhi(k2), blo(v2), c1); c2 = fmaf(blo(k2), bhi(v2), c2); c3 = fmaf(bhi(k2), bhi(v2), c3);
          c0 = fmaf(blo(k3), blo(v3), c0); c1 = fmaf(bhi(k3), blo(v3), c1); c2 = fmaf(blo(k3), bhi(v3), c2); c3 = fmaf(bhi(k3), bhi(v3), c3);
        }
        g_kvp[(j * 16 + r) * 360 + t] = make_float4(c0, c1, c2, c3);
      }
      __syncwarp();
      if (lane == 0) mbar_arrive(sb + B_KVFREE);
      if (warp == 9) TS(3, 3);
      bar_sync(3, 96);
      if (ht == 0) { red_rel(&g_cnt1[j * 32]); wait_ge(&g_cnt1[j * 32], 16 * ep); }
      bar_sync(3, 96);
      if (warp == 9) TS(3, 4);
#pragma unroll 1
      for (int i = ht; i < 360; i += 96) {
        const float* src = reinterpret_cast<const float*>(g_kvp) + j * 16 * 1440 + (r >> 2) * 360 + i;
        float s = 0.f;
#pragma unroll 8
        for (int rr = 0; rr < 16; rr++) s += __ldcg(src + rr * 1440);
        sts32(sb + KVS + i * 4, __float_as_uint(s));
        const int m = i % 40;
        if ((r & 3) == 0 && (m == 36 || m == 37)) g_z[j * 72 + (r >> 2) * 18 + (i / 40) * 2 + m - 36] = s;
      }
      bar_sync(3, 96);
      if (warp == 9) TS(3, 5);
#pragma unroll 1
      for (int t = ht; t < 648; t += 96) {
        const int dp = t / 72, cp = t - dp * 72;
        float c0 = 0.f, c1 = 0.f, c2 = 0.f, c3 = 0.f;
        const uint32_t ka = sb + KVS + dp * 160, wa = sb + WOB + cp * 4;
#pragma unroll
        for (int e2 = 0; e2 < 9; e2++) {
          uint32_t a0, a1, a2, a3;
          lds128(a0, a1, a2, a3, ka + e2 * 16);
          const uint32_t w0 = lds32(wa + e2 * 576), w1 = lds32(wa + e2 * 576 + 288);
          c0 = fmaf(__uint_as_float(a0), blo(w0), c0); c1 = fmaf(__uint_as_float(a0), bhi(w0), c1);
          c2 = fmaf(__uint_as_float(a1), blo(w0), c2); c3 = fmaf(__uint_as_float(a1), bhi(w0), c3);
          c0 = fmaf(__uint_as_float(a2), blo(w1), c0); c1 = fmaf(__uint_as_float(a2), bhi(w1), c1);
          c2 = fmaf(__uint_as_float(a3), blo(w1), c2); c3 = fmaf(__uint_as_float(a3), bhi(w1), c3);
        }
        uint32_t* dst = reinterpret_cast<uint32_t*>(g_M) + (80 * j + 18 * (r >> 2) + 2 * dp) * 288 + 72 * (r & 3) + cp;
        dst[0] = pack2(c0, c1);
        dst[288] = pack2(c2, c3);
      }
      asm volatile("fence.proxy.async;\n" ::: "memory");
      bar_sync(3, 96);
      if (warp == 9) TS(3, 6);
      if (ht == 0) { red_rel(&g_cnt2[j * 32]); wait_ge(&g_cnt2[j * 32], 16 * ep); }
      bar_sync(3, 96);
      if (ht < 72) sts32(sb + ZS + ht * 4, __float_as_uint(__ldcg(g_z + j * 72 + ht)));
      __syncwarp();
      if (lane == 0) mbar_arrive(sb + B_MRDY);
      if (warp == 9) TS(3, 7);
      if (warp == 9) {
        if (lane < 2) {
          int s = 0;
          uint32_t n = 0;
          while (s < 8) {
            if (mbar_test(sb + B_PUB + 16 * s + 8 * lane, 0)) {
              const int c = s == 0 ? 8 : ((j + s) & 7);
              st_rel(&g_flag[((r * 9 + c) * 8 + j) * 2 + lane], ep);
              s++;
            }
            if (++n > SPIN_LIMIT) __trap();
          }
        }
        TS(3, 8);
      } else if (warp == 10) {
        mbar_wait(sb + B_HFREE, 0);
        if (lane < 14) {
          const int s = lane >> 1, w = lane & 1;
          const int idx = ((r * 9 + j) * 8 + ((j - 1 - s) & 7)) * 2 + w;
          bool done = false;
          uint32_t n = 0;
          while (!done) {
            if (ld_acq(&g_flag[idx]) == ep) {
              asm volatile("fence.proxy.async;\n" ::: "memory");
              mbar_expect(sb + B_PFULL + 8 * lane, 8192);
              bulk_g2s(sb + (w ? PS1 : PS0) + s * 8192, g_part + (size_t)idx * 512, 8192, sb + B_PFULL + 8 * lane);
              done = true;
            }
            if (++n > SPIN_LIMIT) __trap();
          }
        }
        TS(3, 9);
      } else {
        if (lane < 8) wait_ge(&g_flag[((r * 9 + 8) * 8 + lane) * 2 + (j >> 2)], ep);
        __syncwarp();
        const uint32_t* src = reinterpret_cast<const uint32_t*>(g_part + (size_t)(((r * 9 + 8) * 8) * 2 + (j >> 2)) * 512 + (j & 3) * 128) + lane;
        const int off0 = ((r * 128 + j * 16 + (lane >> 4) + 8 * (lane & 1)) * D_ + 512 + 8 * ((lane >> 1) & 1) + 2 * ((lane >> 2) & 3)) >> 1;
#pragma unroll 1
        for (int k = 0; k < 16; k++) {
          const int off = off0 + (k & 3) * D_ + (k >> 2) * 8;
          const uint32_t xv = __ldg(reinterpret_cast<const uint32_t*>(p.x) + off);
          uint32_t v[8];
#pragma unroll
          for (int jj = 0; jj < 8; jj++) v[jj] = __ldcg(src + k * 32 + jj * 4096);
          float s0 = blo(xv), s1 = bhi(xv);
#pragma unroll
          for (int jj = 0; jj < 8; jj++) { s0 += blo(v[jj]); s1 += bhi(v[jj]); }
          reinterpret_cast<uint32_t*>(p.out)[off] = pack2(s0, s1);
        }
        TS(3, 10);
        if (lane == 0) g_epoch[blockIdx.x] = ep;
      }
    }
  } else {
    asm volatile("setmaxnreg.inc.sync.aligned.u32 240;\n");
    const int wg = warp >> 2;
    uint32_t a[36][4];
    float dA[32], dB[32];
    const bool l0 = lane == 0;
    constexpr uint64_t dsw128 = mkdesc(sb, 16, 1024, 1);
    constexpr uint64_t dsw64 = mkdesc(sb, SLOT / 2, 512, 2);

    auto issue = [&](float (&d)[32], const uint64_t dbase, const int kstride, const int s, const uint32_t ph) {
      mbar_wait(sb + B_FULL + 8 * s, ph);
      wg_fence();
#pragma unroll
      for (int ks = 0; ks < 6; ks++) wgmma_rs64(d, a[s * 6 + ks], dbase + ((s * SLOT + ks * kstride) >> 4), (s | ks) != 0);
    };
    auto finish = [&](const int rel) {
      wg_commit();
      wg_wait<1>();
      if (rel >= 0 && l0) mbar_arrive(sb + B_EMPTY + 8 * rel);
    };
    auto stW = [&](float (&d)[32], const int s, const uint32_t ph, const int rel) { issue(d, dsw128, 2048, s, ph); finish(rel); };
    auto stF = [&](float (&d)[32], const int s, const uint32_t ph, const int rel) { issue(d, dsw64, 1024, s, ph); finish(rel); };

    TSC(1);
    uint32_t mb0, mb1;
    float dm0, dm1;
    {
      const uint32_t xa = sb + HB + (warp * 16 + (lane & 15)) * 128;
      const uint32_t sw = lane & 7, hi = lane >> 4;
      float c[4][4];
#pragma unroll
      for (int i = 0; i < 4; i++) { c[i][0] = c[i][1] = c[i][2] = c[i][3] = 0.f; }
#pragma unroll
      for (int b = 0; b < 9; b++) {
        mbar_wait(sb + B_X + 8 * b, 0);
#pragma unroll
        for (int kk = 0; kk < 4; kk++) ldsm4(a[4 * b + kk][0], a[4 * b + kk][1], a[4 * b + kk][2], a[4 * b + kk][3], xa + b * 16384 + (((2 * kk + hi) ^ sw) << 4));
#pragma unroll
        for (int kk = 0; kk < 4; kk++) mma16816(c[kk], a[4 * b + kk][0], a[4 * b + kk][1], a[4 * b + kk][2], a[4 * b + kk][3], 0x3F803F80u, 0x3F803F80u);
      }
      TSC(2);
      __syncwarp();
      if (l0) mbar_arrive(sb + B_XDONE);
      const float m0 = ((c[0][0] + c[1][0]) + (c[2][0] + c[3][0])) * (1.f / 576.f);
      const float m1 = ((c[0][2] + c[1][2]) + (c[2][2] + c[3][2])) * (1.f / 576.f);
      mb0 = pack2(m0, m0);
      mb1 = pack2(m1, m1);
      dm0 = m0 - blo(mb0);
      dm1 = m1 - blo(mb1);
    }
    TSC(3);
    float ss0 = 0.f, ss1 = 0.f;
    auto center = [&](const int g) {
#pragma unroll
      for (int ks = 6 * g; ks < 6 * g + 6; ks++) {
        a[ks][0] = bsub2(a[ks][0], mb0); a[ks][1] = bsub2(a[ks][1], mb1);
        a[ks][2] = bsub2(a[ks][2], mb0); a[ks][3] = bsub2(a[ks][3], mb1);
      }
    };
    auto sumsq = [&](const int w0, const int w1) {
#pragma unroll
      for (int w = w0; w < w1; w++) {
        const float lo = blo(a[w >> 2][w & 3]), hi = bhi(a[w >> 2][w & 3]);
        if (w & 1) { ss1 = fmaf(lo, lo, ss1); ss1 = fmaf(hi, hi, ss1); }
        else { ss0 = fmaf(lo, lo, ss0); ss0 = fmaf(hi, hi, ss0); }
      }
      asm volatile("" : "+f"(ss0), "+f"(ss1)::"memory");
    };
    center(0);
#pragma unroll
    for (int s = 0; s < 5; s++) {
      stW(dA, s, 0, s - 1);
      center(s + 1);
      sumsq(24 * (s + 1), 24 * (s + 1) + 18);
    }
    stW(dA, 5, 0, 4);
    sumsq(0, 24);
    TSC(4); GT(1);
    stW(dB, 0, 1, 5);
    sumsq(42, 48); sumsq(66, 72); sumsq(90, 96);
    stW(dB, 1, 1, 0);
    sumsq(114, 120); sumsq(138, 144);
    ss0 += __shfl_xor_sync(0xffffffffu, ss0, 1); ss1 += __shfl_xor_sync(0xffffffffu, ss1, 1);
    ss0 += __shfl_xor_sync(0xffffffffu, ss0, 2); ss1 += __shfl_xor_sync(0xffffffffu, ss1, 2);
    float r0 = rcp(rbf(sqrta(rbf(rbf(fmaxf(ss0 * (1.f / 576.f) - dm0 * dm0, 0.f)) + 1e-5f))));
    float r1 = rcp(rbf(sqrta(rbf(rbf(fmaxf(ss1 * (1.f / 576.f) - dm1 * dm1, 0.f)) + 1e-5f))));
    asm volatile("" : "+f"(r0), "+f"(r1)::"memory");
    const uint32_t tile_off = (warp * 16 + (lane & 15)) * 144 + (lane >> 4) * 16 + (j & 1) * 16;
    mbar_wait(sb + B_XDONE, 0);
#pragma unroll
    for (int s = 2; s < 6; s++) {
      stW(dB, s, 1, s - 1);
      const int t = 2 * (s - 2);
      pin8(dA, 4 * t);
      stsm4(sb + PK_T + tile_off + t * 16, pack2(phi(dA[4 * t] * r0), phi(dA[4 * t + 1] * r0)), pack2(phi(dA[4 * t + 2] * r1), phi(dA[4 * t + 3] * r1)),
            pack2(phi(dA[4 * t + 4] * r0), phi(dA[4 * t + 5] * r0)), pack2(phi(dA[4 * t + 6] * r1), phi(dA[4 * t + 7] * r1)));
    }
    TSC(5);
    {
      stF(dA, 0, 0, 5);
      pin(dB);
#pragma unroll
      for (int t = 0; t < 8; t += 2)
        stsm4(sb + V_T + tile_off + t * 16, pack2(dB[4 * t] * r0, dB[4 * t + 1] * r0), pack2(dB[4 * t + 2] * r1, dB[4 * t + 3] * r1),
              pack2(dB[4 * t + 4] * r0, dB[4 * t + 5] * r0), pack2(dB[4 * t + 6] * r1, dB[4 * t + 7] * r1));
      float dL[12];
      constexpr uint64_t dl = mkdesc(sb + L24_T, 128, 576 * 16, 0);
      mbar_wait(sb + B_LFULL, 0);
#pragma unroll
      for (int s = 1; s < 5; s++) {
        mbar_wait(sb + B_FULL + 8 * s, 0);
        wg_fence();
#pragma unroll
        for (int ks = 9 * (s - 1); ks < 9 * s; ks++) wgmma_rs24(dL, a[ks], dl + ks * 16, ks != 0);
#pragma unroll
        for (int ks = 0; ks < 6; ks++) wgmma_rs64(dA, a[s * 6 + ks], dsw64 + ((s * SLOT + ks * 1024) >> 4), 1);
        finish(s - 1);
      }
      stF(dA, 5, 0, 4);
      pin(dL);
      const uint32_t lo = (warp * 16 + (lane >> 2)) * 144 + ((j & 1) ? 0 : 128) + (lane & 3) * 4;
      sts32(sb + PK_T + lo, pack2(phi(dL[0] * r0), phi(dL[1] * r0)));
      sts32(sb + PK_T + lo + 8 * 144, pack2(phi(dL[2] * r1), phi(dL[3] * r1)));
      sts32(sb + V_T + lo, pack2(dL[4] * r0, dL[5] * r0));
      sts32(sb + V_T + lo + 8 * 144, pack2(dL[6] * r1, dL[7] * r1));
      sts64(sb + Q8 + tid * 8, pack2(dL[8] * r0, dL[9] * r0), pack2(dL[10] * r1, dL[11] * r1));
      __syncwarp();
      if (l0) mbar_arrive(sb + B_KVT);
    }
    TSC(6);
    uint32_t hs = sb + HB + wg * HHALF + (tid & 127) * 16;
    uint32_t hp0, hp1;
    auto epiF = [&](float (&d)[32], const int pc) {
      asm volatile("" : "+f"(d[4 * pc]), "+f"(d[4 * pc + 1]), "+f"(d[4 * pc + 2]), "+f"(d[4 * pc + 3]), "+f"(d[4 * pc + 16]), "+f"(d[4 * pc + 17]),
                   "+f"(d[4 * pc + 18]), "+f"(d[4 * pc + 19])::"memory");
      const float g0 = d[4 * pc] * r0, g1 = d[4 * pc + 1] * r0, g2 = d[4 * pc + 2] * r1, g3 = d[4 * pc + 3] * r1;
      const float L = -1.4426950408889634f;
      const uint32_t h0 = pack2(g0 * (d[4 * pc + 16] * r0) * rcp(1.f + ex2(g0 * L)), g1 * (d[4 * pc + 17] * r0) * rcp(1.f + ex2(g1 * L)));
      const uint32_t h1 = pack2(g2 * (d[4 * pc + 18] * r1) * rcp(1.f + ex2(g2 * L)), g3 * (d[4 * pc + 19] * r1) * rcp(1.f + ex2(g3 * L)));
      if (pc & 1) {
        sts128(hs, hp0, hp1, h0, h1);
        hs += 2048;
      } else {
        hp0 = h0; hp1 = h1;
        asm volatile("" : "+r"(hp0), "+r"(hp1)::"memory");
      }
    };
    stF(dB, 0, 1, 5);
#pragma unroll
    for (int s = 1; s < 5; s++) { epiF(dA, s - 1); stF(dB, s, 1, s - 1); }
#pragma unroll 1
    for (int it = 0; it < 8; it++) {
      stF(dB, 5, 1, 4);
      stF(dA, 0, 0, 5);
      if (it == 6) mbar_wait(sb + B_KVFREE, 0);
#pragma unroll
      for (int s = 1; s < 5; s++) { epiF(dB, s - 1); stF(dA, s, 0, s - 1); }
      stF(dA, 5, 0, 4);
      stF(dB, 0, 1, 5);
#pragma unroll
      for (int s = 1; s < 5; s++) { epiF(dA, s - 1); stF(dB, s, 1, s - 1); }
      TSC(7 + it);
    }
    stF(dB, 5, 1, 4);
    TSC(15);
    const uint32_t hl = sb + HB + wg * HHALF + (tid & 127) * 16;
    auto reload = [&](const int g) {
#pragma unroll
      for (int ks = 6 * g; ks < 6 * g + 6; ks++) lds128(a[ks][0], a[ks][1], a[ks][2], a[ks][3], hl + ks * 2048);
    };
    stW(dA, 0, 0, 5);
#pragma unroll
    for (int s = 1; s < 6; s++) {
      if (s < 5) epiF(dB, s - 1);
      stW(dA, s, 0, s - 1);
      reload(s - 1);
    }
    const uint32_t ot = sb + (wg ? OT1 : OT0);
    const uint64_t do_a = mkdesc(ot, 128, 1280, 0);
    constexpr uint64_t do_b = mkdesc(sb + WO_SLOT, 16, 1024, 1);
    auto stO = [&](float (&d)[32], const uint32_t ph, const int rel) {
      mbar_wait(sb + B_FULL + 48, ph);
      wg_fence();
#pragma unroll
      for (int ks = 0; ks < 5; ks++) wgmma_ss64(d, do_a + ks * 16, do_b + ks * 128);
      finish(rel);
    };
    auto epiP = [&](float (&d)[32], const int step) {
      pin(d);
      const int c = step == 0 ? 8 : ((j + step) & 7);
      uint4* dst = g_part + (size_t)(((r * 9 + c) * 8 + j) * 2 + wg) * 512 + (warp & 3) * 128 + lane;
#pragma unroll
      for (int i = 0; i < 4; i++)
        __stcg(dst + i * 32, make_uint4(pack2(d[8 * i], d[8 * i + 1]), pack2(d[8 * i + 2], d[8 * i + 3]), pack2(d[8 * i + 4], d[8 * i + 5]), pack2(d[8 * i + 6], d[8 * i + 7])));
      __syncwarp();
      if (l0) mbar_arrive(sb + B_PUB + 16 * step + 8 * wg);
    };
    TSC(16);
    {
      stW(dB, 0, 1, 5);
      reload(5);
      float pq[36];
      {
        uint32_t q0, q1;
        lds64(q0, q1, sb + Q8 + tid * 8);
        pin(dA);
        const float ql[4] = {blo(q0), bhi(q0), blo(q1), bhi(q1)};
        const bool odd = j & 1;
#pragma unroll
        for (int i = 0; i < 36; i++) {
          const float rr = (i & 2) ? r1 : r0;
          if (i < 4) pq[i] = odd ? ql[i] : dA[i] * rr;
          else if (i < 32) pq[i] = (odd ? dA[i - 4] : dA[i]) * rr;
          else pq[i] = odd ? dA[i - 4] * rr : ql[i - 32];
        }
        pin(pq);
      }
      fence_async_smem();
      __syncwarp();
      if (l0) mbar_arrive(sb + B_HFREE);
      stW(dB, 1, 1, 0);
#pragma unroll
      for (int i = 0; i < 18; i++) pq[i] = phi(pq[i]);
      pin(pq);
      stW(dB, 2, 1, 1);
#pragma unroll
      for (int i = 18; i < 36; i++) pq[i] = phi(pq[i]);
      pin(pq);
      TSC(17);
      mbar_wait(sb + B_MRDY, 0);
      TSC(18);
      stW(dB, 3, 1, 2);
      const int q = lane & 3;
      float den[8];
#pragma unroll
      for (int i = 0; i < 8; i++) den[i] = 0.f;
#pragma unroll
      for (int t = 0; t < 9; t++) {
        uint32_t z0, z1;
        lds64(z0, z1, sb + ZS + t * 32 + q * 8);
        const float s0 = fmaf(pq[4 * t], __uint_as_float(z0), pq[4 * t + 1] * __uint_as_float(z1));
        const float s1 = fmaf(pq[4 * t + 2], __uint_as_float(z0), pq[4 * t + 3] * __uint_as_float(z1));
        const int lo = (8 * t) / 18, hi = (8 * t + 7) / 18;
        if (lo == hi) { den[2 * lo] += s0; den[2 * lo + 1] += s1; }
        else if (8 * t + 2 * q >= 18 * hi) { den[2 * hi] += s0; den[2 * hi + 1] += s1; }
        else { den[2 * lo] += s0; den[2 * lo + 1] += s1; }
      }
      pin(den);
      bar_sync(1 + wg, 128);
      stW(dB, 4, 1, 3);
#pragma unroll
      for (int i = 0; i < 8; i++) den[i] += __shfl_xor_sync(0xffffffffu, den[i], 1);
#pragma unroll
      for (int i = 0; i < 8; i++) den[i] = rcp(den[i] + __shfl_xor_sync(0xffffffffu, den[i], 2) + 1e-6f);
      const uint32_t oa = ot + ((warp & 3) * 2 + ((lane >> 3) & 1)) * 1280 + (lane >> 4) * 128 + (lane & 7) * 16;
#pragma unroll
      for (int t = 0; t < 10; t += 2) {
        uint32_t o[4];
#pragma unroll
        for (int z = 0; z < 2; z++) {
          const int tt = t + z;
          if (tt < 9) {
            const int lo = (8 * tt) / 18, hi = (8 * tt + 7) / 18;
            const bool up = lo != hi && 8 * tt + 2 * q >= 18 * hi;
            const float i0 = up ? den[2 * hi] : den[2 * lo], i1 = up ? den[2 * hi + 1] : den[2 * lo + 1];
            o[2 * z] = pack2(pq[4 * tt] * i0, pq[4 * tt + 1] * i0);
            o[2 * z + 1] = pack2(pq[4 * tt + 2] * i1, pq[4 * tt + 3] * i1);
          } else {
            o[2 * z] = 0; o[2 * z + 1] = 0;
          }
        }
        stsm4(oa + t * 128, o[0], o[1], o[2], o[3]);
      }
      fence_async_smem();
      stW(dB, 5, 1, 4);
      bar_sync(1 + wg, 128);
      stO(dB, 0, 5);
    }
    stW(dA, 0, 0, 6);
    epiP(dB, 0);
    TSC(19);
#pragma unroll 1
    for (int it = 0; it < 3; it++) {
#pragma unroll
      for (int s = 1; s < 6; s++) stW(dA, s, 0, s - 1);
      stO(dA, 1, 5);
      stW(dB, 0, 1, 6);
      epiP(dA, 1 + 2 * it);
#pragma unroll
      for (int s = 1; s < 6; s++) stW(dB, s, 1, s - 1);
      stO(dB, 0, 5);
      stW(dA, 0, 0, 6);
      epiP(dB, 2 + 2 * it);
      TSC(20 + it);
    }
#pragma unroll
    for (int s = 1; s < 6; s++) stW(dA, s, 0, s - 1);
    stO(dA, 1, 5);
    stW(dB, 0, 1, 6);
    epiP(dA, 7);
    TSC(23);
    {
      const __nv_bfloat16* xp = p.x + (size_t)(r * 128 + warp * 16 + (lane >> 2)) * D_ + 64 * j + 2 * (lane & 3);
      uint32_t xv[16];
#pragma unroll
      for (int t = 0; t < 8; t++) {
        xv[2 * t] = __ldg(reinterpret_cast<const uint32_t*>(xp + 8 * t));
        xv[2 * t + 1] = __ldg(reinterpret_cast<const uint32_t*>(xp + 8 * D_ + 8 * t));
      }
      stW(dB, 1, 1, -1);
      stW(dB, 2, 1, -1);
#pragma unroll
      for (int i = 0; i < 16; i++) { dA[2 * i] = blo(xv[i]); dA[2 * i + 1] = bhi(xv[i]); }
    }
    const uint32_t ps = sb + (wg ? PS1 : PS0) + (warp & 3) * 2048;
    auto addp = [&](const int s) {
      mbar_wait(sb + B_PFULL + 16 * s + 8 * wg, 0);
#pragma unroll
      for (int i = 0; i < 4; i++) {
        uint32_t v0, v1, v2, v3;
        lds128(v0, v1, v2, v3, ps + s * 8192 + i * 512 + lane * 16);
        dA[8 * i] += blo(v0); dA[8 * i + 1] += bhi(v0); dA[8 * i + 2] += blo(v1); dA[8 * i + 3] += bhi(v1);
        dA[8 * i + 4] += blo(v2); dA[8 * i + 5] += bhi(v2); dA[8 * i + 6] += blo(v3); dA[8 * i + 7] += bhi(v3);
      }
      pin(dA);
    };
    addp(0);
    stW(dB, 3, 1, -1);
    addp(1); addp(2);
    stW(dB, 4, 1, -1);
    addp(3); addp(4);
    stW(dB, 5, 1, -1);
    addp(5);
    stO(dB, 0, -1);
    TSC(24);
    addp(6);
    TSC(25);
    wg_wait<0>();
    TSC(26); GT(2);
    pin(dB);
    {
      __syncwarp();
      const int row = lane & 15;
#pragma unroll
      for (int t = 0; t < 8; t += 2)
        stsm4(ps + row * 128 + (((t + (lane >> 4)) ^ (row & 7)) << 4),
              pack2(dA[4 * t] + dB[4 * t], dA[4 * t + 1] + dB[4 * t + 1]), pack2(dA[4 * t + 2] + dB[4 * t + 2], dA[4 * t + 3] + dB[4 * t + 3]),
              pack2(dA[4 * t + 4] + dB[4 * t + 4], dA[4 * t + 5] + dB[4 * t + 5]), pack2(dA[4 * t + 6] + dB[4 * t + 6], dA[4 * t + 7] + dB[4 * t + 7]));
      __syncwarp();
#pragma unroll
      for (int i = 0; i < 4; i++) {
        const int rr = i * 4 + (lane >> 3), ch = lane & 7;
        uint4 v;
        lds128(v.x, v.y, v.z, v.w, ps + rr * 128 + ((ch ^ (rr & 7)) << 4));
        *reinterpret_cast<uint4*>(p.out + (size_t)(r * 128 + warp * 16 + rr) * D_ + 64 * j + ch * 8) = v;
      }
    }
    TSC(27); GT(3);
  }
}

typedef CUresult (*EncodeFn)(CUtensorMap*, CUtensorMapDataType, cuuint32_t, void*, const cuuint64_t*, const cuuint64_t*, const cuuint32_t*,
                             const cuuint32_t*, CUtensorMapInterleave, CUtensorMapSwizzle, CUtensorMapL2promotion, CUtensorMapFloatOOBfill);

CUtensorMap make_map(EncodeFn enc, const void* ptr, int rows, int cols, int brow, int bcol, CUtensorMapSwizzle sw) {
  CUtensorMap m;
  cuuint64_t gd[2] = {(cuuint64_t)cols, (cuuint64_t)rows};
  cuuint64_t gs[1] = {(cuuint64_t)cols * 2};
  cuuint32_t bd[2] = {(cuuint32_t)bcol, (cuuint32_t)brow};
  cuuint32_t es[2] = {1, 1};
  enc(&m, CU_TENSOR_MAP_DATA_TYPE_BFLOAT16, 2, const_cast<void*>(ptr), gd, gs, bd, es, CU_TENSOR_MAP_INTERLEAVE_NONE, sw,
      CU_TENSOR_MAP_L2_PROMOTION_L2_128B, CU_TENSOR_MAP_FLOAT_OOB_FILL_NONE);
  return m;
}

}

extern "C" void kernel_launch(void* const* d_in, const int* in_sizes, int n_in, void* d_out, int out_size) {
  (void)in_sizes; (void)n_in; (void)out_size;
  static EncodeFn enc = nullptr;
  static void* m_ptr = nullptr;
  if (!enc) {
    cudaGetSymbolAddress(&m_ptr, g_M);
    cudaDriverEntryPointQueryResult qr;
    cudaGetDriverEntryPoint("cuTensorMapEncodeTiled", (void**)&enc, cudaEnableDefault, &qr);
    cudaFuncSetAttribute(fused_block_kernel, cudaFuncAttributeMaxDynamicSharedMemorySize, SMEM_BYTES);
  }
  Params p;
  p.x = (const __nv_bfloat16*)d_in[0];
  p.wqkv = (const __nv_bfloat16*)d_in[1];
  p.wo = (const __nv_bfloat16*)d_in[2];
  p.w1 = (const __nv_bfloat16*)d_in[4];
  p.w3 = (const __nv_bfloat16*)d_in[5];
  p.w2 = (const __nv_bfloat16*)d_in[6];
  p.out = (__nv_bfloat16*)d_out;
  const CUtensorMap m_qkv = make_map(enc, p.wqkv, D_, 3 * D_, 96, 64, CU_TENSOR_MAP_SWIZZLE_128B);
  const CUtensorMap m_w1 = make_map(enc, p.w1, D_, F_, 96, 32, CU_TENSOR_MAP_SWIZZLE_64B);
  const CUtensorMap m_w3 = make_map(enc, p.w3, D_, F_, 96, 32, CU_TENSOR_MAP_SWIZZLE_64B);
  const CUtensorMap m_w2 = make_map(enc, p.w2, F_, D_, 96, 64, CU_TENSOR_MAP_SWIZZLE_128B);
  const CUtensorMap m_M = make_map(enc, m_ptr, 8 * 80, D_, 80, 64, CU_TENSOR_MAP_SWIZZLE_128B);
  const CUtensorMap m_x = make_map(enc, p.x, 2048, D_, 128, 64, CU_TENSOR_MAP_SWIZZLE_128B);
  fused_block_kernel<<<128, NTHREADS, SMEM_BYTES>>>(m_qkv, m_w1, m_w3, m_w2, m_M, m_x, p);
}
```

```cpp
#include <cuda_runtime.h>
#include <cuda.h>
#include <cuda_bf16.h>
#include <stdint.h>

namespace {

constexpr int D_ = 576, F_ = 4608;
constexpr int NTHREADS = 384;

constexpr uint32_t SLOT = 12288;
constexpr uint32_t HB = 6 * SLOT;
constexpr uint32_t HHALF = 73728;
constexpr uint32_t PK_T = HB + 45056;
constexpr uint32_t V_T = HB + HHALF + 18432;
constexpr uint32_t L24_T = HB + 16384;
constexpr uint32_t WO_SLOT = HB + 67584;
constexpr uint32_t OT0 = HB, OT1 = HB + 137216;
constexpr uint32_t PS0 = HB + 10240, PS1 = HB + 79872;
constexpr uint32_t Q8 = HB + 2 * HHALF;
constexpr uint32_t WOB = Q8 + 2048;
constexpr uint32_t KVS = WOB + 5184;
constexpr uint32_t ZS = KVS + 1440;
constexpr uint32_t BARS = ZS + 288;
constexpr uint32_t SMEM_BYTES = BARS + 512;

constexpr uint32_t B_FULL = BARS;
constexpr uint32_t B_X = BARS + 8 * 7;
constexpr uint32_t B_PFULL = BARS + 8 * 16;
constexpr uint32_t B_EMPTY = BARS + 8 * 30;
constexpr uint32_t B_PUB = BARS + 8 * 37;
constexpr uint32_t B_XDONE = BARS + 8 * 45;
constexpr uint32_t B_KVT = BARS + 8 * 46;
constexpr uint32_t B_KVD = BARS + 8 * 47;
constexpr uint32_t B_HFREE = BARS + 8 * 48;
constexpr uint32_t B_LFULL = BARS + 8 * 49;
constexpr uint32_t B_MRDY = BARS + 8 * 50;

constexpr uint32_t SPIN_LIMIT = 1u << 22;

__device__ uint4 g_part[16 * 9 * 8 * 2 * 512];
__device__ float4 g_kvp[8 * 16 * 1280];
__device__ __align__(128) __nv_bfloat16 g_M[8 * 80 * 576];
__device__ __align__(16) float g_z[8 * 72];
__device__ uint32_t g_cnt1[8 * 32], g_cnt2[8 * 32];
__device__ uint32_t g_flag[16 * 9 * 8];
__device__ uint32_t g_epoch[128];

#define TS(slot, i)
#define TSC(i)
#define GT(i)

__device__ __forceinline__ void wg_fence() { asm volatile("wgmma.fence.sync.aligned;\n" ::: "memory"); }
__device__ __forceinline__ void wg_commit() { asm volatile("wgmma.commit_group.sync.aligned;\n" ::: "memory"); }
template <int N> __device__ __forceinline__ void wg_wait() { asm volatile("wgmma.wait_group.sync.aligned %0;\n" ::"n"(N) : "memory"); }
__host__ __device__ constexpr uint64_t mkdesc(uint32_t addr, uint32_t lbo, uint32_t sbo, uint32_t sw) {
  return (uint64_t)((addr & 0x3FFFF) >> 4) | ((uint64_t)(lbo >> 4) << 16) | ((uint64_t)(sbo >> 4) << 32) | ((uint64_t)sw << 62);
}
__device__ __forceinline__ void mbar_init(uint32_t a, uint32_t c) { asm volatile("mbarrier.init.shared::cta.b64 [%0], %1;\n" ::"r"(a), "r"(c) : "memory"); }
__device__ __forceinline__ void mbar_expect(uint32_t a, uint32_t b) { asm volatile("mbarrier.arrive.expect_tx.shared::cta.b64 _, [%0], %1;\n" ::"r"(a), "r"(b) : "memory"); }
__device__ __forceinline__ void mbar_arrive(uint32_t a) { asm volatile("mbarrier.arrive.shared::cta.b64 _, [%0];\n" ::"r"(a) : "memory"); }
__device__ __forceinline__ void mbar_wait(uint32_t a, uint32_t ph) {
  asm volatile(
      "{\n.reg .pred p;\n.reg .u32 n;\n"
      "mbarrier.try_wait.parity.shared::cta.b64 p, [%0], %1;\n"
      "@p bra DONE;\n"
      "mov.u32 n, 0;\n"
      "LOOP:\n"
      "mbarrier.try_wait.parity.shared::cta.b64 p, [%0], %1;\n"
      "@p bra DONE;\n"
      "add.u32 n, n, 1;\n"
      "setp.lt.u32 p, n, %2;\n"
      "@p bra LOOP;\n"
      "trap;\n"
      "DONE:\n}\n" ::"r"(a), "r"(ph), "n"(SPIN_LIMIT) : "memory");
}
__device__ __forceinline__ void cp_async16(uint32_t dst, const void* src) {
  asm volatile("cp.async.cg.shared.global [%0], [%1], 16;\n" ::"r"(dst), "l"(src) : "memory");
}
__device__ __forceinline__ void tma2d(uint32_t dst, const CUtensorMap* m, int c0, int c1, uint32_t bar) {
  asm volatile("cp.async.bulk.tensor.2d.shared::cluster.global.mbarrier::complete_tx::bytes [%0], [%1, {%3, %4}], [%2];\n" ::"r"(dst), "l"(m), "r"(bar), "r"(c0), "r"(c1) : "memory");
}
__device__ __forceinline__ void bulk_g2s(uint32_t dst, const void* src, uint32_t bytes, uint32_t bar) {
  asm volatile("cp.async.bulk.shared::cluster.global.mbarrier::complete_tx::bytes [%0], [%1], %2, [%3];\n" ::"r"(dst), "l"(src), "r"(bytes), "r"(bar) : "memory");
}
__device__ __forceinline__ void prefetch_l2(const void* p) { asm volatile("prefetch.global.L2 [%0];\n" ::"l"(p)); }
__device__ __forceinline__ void fence_async_smem() { asm volatile("fence.proxy.async.shared::cta;\n" ::: "memory"); }
__device__ __forceinline__ void bar_sync(int id, int n) { asm volatile("bar.sync %0, %1;\n" ::"r"(id), "r"(n) : "memory"); }
__device__ __forceinline__ void ldsm4(uint32_t& r0, uint32_t& r1, uint32_t& r2, uint32_t& r3, uint32_t a) {
  asm volatile("ldmatrix.sync.aligned.m8n8.x4.shared.b16 {%0,%1,%2,%3}, [%4];\n" : "=r"(r0), "=r"(r1), "=r"(r2), "=r"(r3) : "r"(a) : "memory");
}
__device__ __forceinline__ void stsm4(uint32_t a, uint32_t r0, uint32_t r1, uint32_t r2, uint32_t r3) {
  asm volatile("stmatrix.sync.aligned.m8n8.x4.shared.b16 [%0], {%1,%2,%3,%4};\n" ::"r"(a), "r"(r0), "r"(r1), "r"(r2), "r"(r3) : "memory");
}
__device__ __forceinline__ void sts128(uint32_t a, uint32_t r0, uint32_t r1, uint32_t r2, uint32_t r3) {
  asm volatile("st.shared.v4.b32 [%0], {%1,%2,%3,%4};\n" ::"r"(a), "r"(r0), "r"(r1), "r"(r2), "r"(r3) : "memory");
}
__device__ __forceinline__ void lds128(uint32_t& r0, uint32_t& r1, uint32_t& r2, uint32_t& r3, uint32_t a) {
  asm volatile("ld.shared.v4.b32 {%0,%1,%2,%3}, [%4];\n" : "=r"(r0), "=r"(r1), "=r"(r2), "=r"(r3) : "r"(a) : "memory");
}
__device__ __forceinline__ void sts64(uint32_t a, uint32_t r0, uint32_t r1) { asm volatile("st.shared.v2.b32 [%0], {%1,%2};\n" ::"r"(a), "r"(r0), "r"(r1) : "memory"); }
__device__ __forceinline__ void lds64(uint32_t& r0, uint32_t& r1, uint32_t a) { asm volatile("ld.shared.v2.b32 {%0,%1}, [%2];\n" : "=r"(r0), "=r"(r1) : "r"(a) : "memory"); }
__device__ __forceinline__ uint32_t lds32(uint32_t a) { uint32_t v; asm volatile("ld.shared.b32 %0, [%1];\n" : "=r"(v) : "r"(a) : "memory"); return v; }
__device__ __forceinline__ void sts32(uint32_t a, uint32_t r0) { asm volatile("st.shared.b32 [%0], %1;\n" ::"r"(a), "r"(r0) : "memory"); }
__device__ __forceinline__ void mma16816(float (&c)[4], uint32_t a0, uint32_t a1, uint32_t a2, uint32_t a3, uint32_t b0, uint32_t b1) {
  asm volatile("mma.sync.aligned.m16n8k16.row.col.f32.bf16.bf16.f32 {%0,%1,%2,%3}, {%4,%5,%6,%7}, {%8,%9}, {%0,%1,%2,%3};\n"
               : "+f"(c[0]), "+f"(c[1]), "+f"(c[2]), "+f"(c[3]) : "r"(a0), "r"(a1), "r"(a2), "r"(a3), "r"(b0), "r"(b1));
}
__device__ __forceinline__ uint32_t pack2(float lo, float hi) {
  uint32_t r;
  asm("cvt.rn.bf16x2.f32 %0, %1, %2;\n" : "=r"(r) : "f"(hi), "f"(lo));
  return r;
}
__device__ __forceinline__ float blo(uint32_t w) { return __uint_as_float(w << 16); }
__device__ __forceinline__ float bhi(uint32_t w) { return __uint_as_float(w & 0xffff0000u); }
__device__ __forceinline__ float rbf(float x) { return __bfloat162float(__float2bfloat16_rn(x)); }
__device__ __forceinline__ float ex2(float x) { float r; asm("ex2.approx.ftz.f32 %0, %1;\n" : "=f"(r) : "f"(x)); return r; }
__device__ __forceinline__ float rcp(float x) { float r; asm("rcp.approx.ftz.f32 %0, %1;\n" : "=f"(r) : "f"(x)); return r; }
__device__ __forceinline__ float sqrta(float x) { float r; asm("sqrt.approx.ftz.f32 %0, %1;\n" : "=f"(r) : "f"(x)); return r; }
__device__ __forceinline__ uint32_t bsub2(uint32_t a, uint32_t b) { uint32_t r; asm("sub.rn.bf16x2 %0, %1, %2;\n" : "=r"(r) : "r"(a), "r"(b)); return r; }
__device__ __forceinline__ uint32_t ld_acq(const uint32_t* p) { uint32_t v; asm volatile("ld.acquire.gpu.global.u32 %0, [%1];\n" : "=r"(v) : "l"(p) : "memory"); return v; }
__device__ __forceinline__ void st_rel(uint32_t* p, uint32_t v) { asm volatile("st.release.gpu.global.u32 [%0], %1;\n" ::"l"(p), "r"(v) : "memory"); }
__device__ __forceinline__ void red_rel(uint32_t* p) { asm volatile("red.release.gpu.global.add.u32 [%0], 1;\n" ::"l"(p) : "memory"); }
__device__ __forceinline__ void wait_ge(const uint32_t* p, uint32_t target) {
  uint32_t n = 0;
  while ((int32_t)(ld_acq(p) - target) < 0) {
    __nanosleep(64);
    if (++n > SPIN_LIMIT) __trap();
  }
}
__device__ __forceinline__ float phi(float a, float r, float rl) { return fmaf(fmaxf(a, 0.f), r, __saturatef(ex2(a * rl) + 1e-6f)); }

#define ACC8(d, o) "+f"(d[o + 0]), "+f"(d[o + 1]), "+f"(d[o + 2]), "+f"(d[o + 3]), "+f"(d[o + 4]), "+f"(d[o + 5]), "+f"(d[o + 6]), "+f"(d[o + 7])
#define REGS32 "{%0,%1,%2,%3,%4,%5,%6,%7,%8,%9,%10,%11,%12,%13,%14,%15,%16,%17,%18,%19,%20,%21,%22,%23,%24,%25,%26,%27,%28,%29,%30,%31}"
__device__ __forceinline__ void wgmma_rs64(float (&d)[32], const uint32_t (&a)[4], uint64_t db, int acc) {
  asm volatile("{\n.reg .pred p;\nsetp.ne.b32 p, %37, 0;\n"
               "wgmma.mma_async.sync.aligned.m64n64k16.f32.bf16.bf16 " REGS32 ", {%32,%33,%34,%35}, %36, p, 1, 1, 1;\n}\n"
               : ACC8(d, 0), ACC8(d, 8), ACC8(d, 16), ACC8(d, 24)
               : "r"(a[0]), "r"(a[1]), "r"(a[2]), "r"(a[3]), "l"(db), "r"(acc));
}
__device__ __forceinline__ void wgmma_ss64(float (&d)[32], uint64_t da, uint64_t db) {
  asm volatile("wgmma.mma_async.sync.aligned.m64n64k16.f32.bf16.bf16 " REGS32 ", %32, %33, 1, 1, 1, 0, 1;\n"
               : ACC8(d, 0), ACC8(d, 8), ACC8(d, 16), ACC8(d, 24)
               : "l"(da), "l"(db));
}
__device__ __forceinline__ void wgmma_rs24(float (&d)[12], const uint32_t (&a)[4], uint64_t db, int acc) {
  asm volatile("{\n.reg .pred p;\nsetp.ne.b32 p, %17, 0;\n"
               "wgmma.mma_async.sync.aligned.m64n24k16.f32.bf16.bf16 {%0,%1,%2,%3,%4,%5,%6,%7,%8,%9,%10,%11}, {%12,%13,%14,%15}, %16, p, 1, 1, 1;\n}\n"
               : ACC8(d, 0), "+f"(d[8]), "+f"(d[9]), "+f"(d[10]), "+f"(d[11])
               : "r"(a[0]), "r"(a[1]), "r"(a[2]), "r"(a[3]), "l"(db), "r"(acc));
}
__device__ __forceinline__ void wgmma_ss40tt(float (&d)[20], uint64_t da, uint64_t db, int acc) {
  asm volatile("{\n.reg .pred p;\nsetp.ne.b32 p, %22, 0;\n"
               "wgmma.mma_async.sync.aligned.m64n40k16.f32.bf16.bf16 {%0,%1,%2,%3,%4,%5,%6,%7,%8,%9,%10,%11,%12,%13,%14,%15,%16,%17,%18,%19}, %20, %21, p, 1, 1, 1, 1;\n}\n"
               : ACC8(d, 0), ACC8(d, 8), "+f"(d[16]), "+f"(d[17]), "+f"(d[18]), "+f"(d[19])
               : "l"(da), "l"(db), "r"(acc));
}
template <int N> __device__ __forceinline__ void pin(float (&d)[N]) {
#pragma unroll
  for (int i = 0; i < N; i++) asm volatile("" : "+f"(d[i])::"memory");
}

__device__ __forceinline__ void pin8(float (&d)[32], const int o) { asm volatile("" : ACC8(d, o)::"memory"); }

struct Params {
  const __nv_bfloat16* x;
  const __nv_bfloat16* wqkv;
  const __nv_bfloat16* wo;
  const __nv_bfloat16* w1;
  const __nv_bfloat16* w3;
  const __nv_bfloat16* w2;
  __nv_bfloat16* out;
};

__global__ void __launch_bounds__(NTHREADS, 1)
fused_block_kernel(const __grid_constant__ CUtensorMap m_qkv, const __grid_constant__ CUtensorMap m_w1,
                   const __grid_constant__ CUtensorMap m_w3, const __grid_constant__ CUtensorMap m_w2,
                   const __grid_constant__ CUtensorMap m_M, const __grid_constant__ CUtensorMap m_x, const Params p) {
  extern __shared__ __align__(1024) uint8_t smem_raw[];
  constexpr uint32_t sb = 1024;
  if ((uint32_t)__cvta_generic_to_shared(smem_raw) != sb) __trap();
  const int tid = threadIdx.x, warp = tid >> 5, lane = tid & 31;
  const int r = blockIdx.x >> 3, j = blockIdx.x & 7;

  GT(0); TSC(0);
  const int cmain = 72 * j + 8 * (j & 1);
  if (tid >= 256 && tid < 256 + 51) {
    const int i = tid - 256;
    if (i == 0) asm volatile("prefetch.tensormap [%0];\n" ::"l"(&m_x) : "memory");
    if (i == 32) asm volatile("prefetch.tensormap [%0];\n" ::"l"(&m_qkv) : "memory");
    mbar_init(sb + BARS + 8 * i, i < 30 ? 1 : i < 49 ? 8 : i == 49 ? 96 : 3);
    asm volatile("fence.mbarrier_init.release.cluster;\n" ::: "memory");
  }
  __syncthreads();

  if (warp >= 8) {
    asm volatile("setmaxnreg.dec.sync.aligned.u32 24;\n");
    if (warp == 8) {
      if (lane == 0) {
#pragma unroll
        for (int b = 0; b < 9; b++) {
          mbar_expect(sb + B_X + 8 * b, 16384);
          tma2d(sb + HB + b * 16384, &m_x, 64 * b, 128 * r, sb + B_X + 8 * b);
        }
#pragma unroll
        for (int s = 0; s < 6; s++) {
          mbar_expect(sb + B_FULL + 8 * s, SLOT);
          tma2d(sb + s * SLOT, &m_qkv, D_ + cmain, 96 * s, sb + B_FULL + 8 * s);
        }
#pragma unroll
        for (int s = 0; s < 6; s++) {
          mbar_wait(sb + B_EMPTY + 8 * s, 0);
          mbar_expect(sb + B_FULL + 8 * s, SLOT);
          tma2d(sb + s * SLOT, &m_qkv, 2 * D_ + cmain, 96 * s, sb + B_FULL + 8 * s);
        }
#pragma unroll 1
        for (int n = 0; n < 18; n++) {
          const int col = 576 * j + 32 * n;
#pragma unroll
          for (int s = 0; s < 6; s++) {
            mbar_wait(sb + B_EMPTY + 8 * s, (n & 1) ^ 1);
            mbar_expect(sb + B_FULL + 8 * s, SLOT);
            tma2d(sb + s * SLOT, &m_w1, col, 96 * s, sb + B_FULL + 8 * s);
            tma2d(sb + s * SLOT + SLOT / 2, &m_w3, col, 96 * s, sb + B_FULL + 8 * s);
          }
        }
#pragma unroll
        for (int s = 0; s < 6; s++) {
          mbar_wait(sb + B_EMPTY + 8 * s, 1);
          mbar_expect(sb + B_FULL + 8 * s, SLOT);
          tma2d(sb + s * SLOT, &m_qkv, cmain, 96 * s, sb + B_FULL + 8 * s);
        }
#pragma unroll 1
        for (int n = 0; n < 9; n++) {
          const int col = n == 0 ? 512 : 64 * ((j + n) & 7);
#pragma unroll
          for (int s = 0; s < 6; s++) {
            mbar_wait(sb + B_EMPTY + 8 * s, n & 1);
            mbar_expect(sb + B_FULL + 8 * s, SLOT);
            tma2d(sb + s * SLOT, &m_w2, col, 576 * j + 96 * s, sb + B_FULL + 8 * s);
          }
          if (n == 0) {
            mbar_wait(sb + B_HFREE, 0);
            mbar_wait(sb + B_MRDY, 0);
            asm volatile("fence.proxy.async;\n" ::: "memory");
          }
          mbar_wait(sb + B_EMPTY + 48, (n & 1) ^ 1);
          mbar_expect(sb + B_FULL + 48, 80 * 128);
          tma2d(sb + WO_SLOT, &m_M, col, 80 * j, sb + B_FULL + 48);
        }
      }
    } else {
      const int ht = tid - 288;
      const uint32_t ep = g_epoch[blockIdx.x] + 1;
      if (ht < 72) {
        const __nv_bfloat16* w = p.wqkv + (size_t)(36 * r + (ht >> 1)) * (3 * D_) + 72 * j + (ht & 1) * 64;
        prefetch_l2(w + 2 * D_); prefetch_l2(w + D_); prefetch_l2(w);
      }
      if (ht < 90) {
        const int e = ht / 18, c = ht - e * 18;
        const __nv_bfloat16* w = p.wo + (size_t)(72 * j + 18 * (r >> 2) + e) * D_ + 144 * (r & 3) + c * 8;
#pragma unroll
        for (int i = 0; i < 4; i++)
          if (i < 3 || ht < 54) cp_async16(sb + WOB + ht * 16 + i * 90 * 16, w + i * 5 * D_);
      }
      const __nv_bfloat16* wl = p.wqkv + (size_t)ht * (3 * D_) + 72 * j + ((j & 1) ? 0 : 64);
      const __nv_bfloat16* wf = (ht < 36 ? p.w1 : p.w3) + (size_t)(36 * r + (ht < 36 ? ht : ht - 36)) * F_ + 576 * j;
      mbar_wait(sb + B_X + 8 * 8, 0);
      if (ht < 72) {
#pragma unroll
        for (int cb = 0; cb < 9; cb++) prefetch_l2(wf + cb * 64);
      }
      mbar_wait(sb + B_XDONE, 0);
#pragma unroll
      for (int g = 0; g < 3; g++)
#pragma unroll
        for (int m = 0; m < 6; m++) cp_async16(sb + L24_T + g * 9216 + m * 96 * 16 + ht * 16, wl + (size_t)m * 96 * 3 * D_ + (g == 2 ? 0 : (g + 1) * D_));
      if (ht < 64) {
#pragma unroll
        for (int i = 0; i < 4; i++) sts128(sb + V_T - 2048 + (i >> 1) * 20480 + (i & 1) * 1024 + ht * 16, 0x3F803F80u, 0x3F803F80u, 0x3F803F80u, 0x3F803F80u);
      }
      {
        const __nv_bfloat16* w = p.w2 + (size_t)(576 * j + 36 * r) * D_ + ht * 64;
#pragma unroll
        for (int i = 0; i < 4; i++)
          if (i < 3 || ht < 36) prefetch_l2(w + i * 96 * 64);
      }
      asm volatile("cp.async.wait_all;\n" ::: "memory");
      fence_async_smem();
      mbar_arrive(sb + B_LFULL);
      if (warp == 9) TS(3, 1);

      if (ht == 0) {
        mbar_wait(sb + B_KVD, 0);
        red_rel(&g_cnt1[j * 32]);
        wait_ge(&g_cnt1[j * 32], 16 * ep);
      }
      bar_sync(3, 96);
      if (warp == 9) TS(3, 4);
#pragma unroll 1
      for (int i = ht; i < 171; i += 96) {
        const int dp = i / 19, el = i - dp * 19, hd = r >> 2, w = hd >> 1;
        const int d = 18 * hd + 2 * dp - 32 * w;
        const int m = el == 18 ? 56 * w : 18 * hd + el + 8 - 24 * w;
        const float2* src = reinterpret_cast<const float2*>(g_kvp + j * 16 * 1280 + ((w * 4 + (m >> 4)) * 5 + (d >> 3)) * 32 + (m & 7) * 4 + ((d & 7) >> 1)) + ((m >> 3) & 1);
        float s0 = 0.f, s1 = 0.f;
#pragma unroll 1
        for (int r4 = 0; r4 < 4; r4++) {
          const float2 v0 = __ldcg(src), v1 = __ldcg(src + 2560), v2 = __ldcg(src + 2 * 2560), v3 = __ldcg(src + 3 * 2560);
          s0 += (v0.x + v1.x) + (v2.x + v3.x);
          s1 += (v0.y + v1.y) + (v2.y + v3.y);
          src += 4 * 2560;
        }
        sts64(sb + KVS + dp * 160 + el * 8, __float_as_uint(s0), __float_as_uint(s1));
        if ((r & 3) == 0 && el == 18) *reinterpret_cast<float2*>(g_z + j * 72 + hd * 18 + dp * 2) = make_float2(s0, s1);
      }
      bar_sync(3, 96);
      if (warp == 9) TS(3, 5);
#pragma unroll 1
      for (int t = ht; t < 648; t += 96) {
        const int dp = t / 72, cp = t - dp * 72;
        float c0 = 0.f, c1 = 0.f, c2 = 0.f, c3 = 0.f;
        const uint32_t ka = sb + KVS + dp * 160, wa = sb + WOB + cp * 4;
#pragma unroll
        for (int e2 = 0; e2 < 9; e2++) {
          uint32_t a0, a1, a2, a3;
          lds128(a0, a1, a2, a3, ka + e2 * 16);
          const uint32_t w0 = lds32(wa + e2 * 576), w1 = lds32(wa + e2 * 576 + 288);
          c0 = fmaf(__uint_as_float(a0), blo(w0), c0); c1 = fmaf(__uint_as_float(a0), bhi(w0), c1);
          c2 = fmaf(__uint_as_float(a1), blo(w0), c2); c3 = fmaf(__uint_as_float(a1), bhi(w0), c3);
          c0 = fmaf(__uint_as_float(a2), blo(w1), c0); c1 = fmaf(__uint_as_float(a2), bhi(w1), c1);
          c2 = fmaf(__uint_as_float(a3), blo(w1), c2); c3 = fmaf(__uint_as_float(a3), bhi(w1), c3);
        }
        uint32_t* dst = reinterpret_cast<uint32_t*>(g_M) + (80 * j + 18 * (r >> 2) + 2 * dp) * 288 + 72 * (r & 3) + cp;
        dst[0] = pack2(c0, c1);
        dst[288] = pack2(c2, c3);
      }
      asm volatile("fence.proxy.async;\n" ::: "memory");
      bar_sync(3, 96);
      if (warp == 9) TS(3, 6);
      if (ht == 0) { red_rel(&g_cnt2[j * 32]); wait_ge(&g_cnt2[j * 32], 16 * ep); }
      bar_sync(3, 96);
      if (ht < 72) sts32(sb + ZS + ht * 4, __float_as_uint(__ldcg(g_z + j * 72 + ht)));
      __syncwarp();
      if (lane == 0) mbar_arrive(sb + B_MRDY);
      if (warp == 9) TS(3, 7);
      if (warp == 9) {
        if (lane == 0) {
#pragma unroll 1
          for (int s = 0; s < 8; s++) {
            mbar_wait(sb + B_PUB + 8 * s, 0);
            st_rel(&g_flag[(r * 9 + (s == 0 ? 8 : ((j + s) & 7))) * 8 + j], ep);
          }
        }
        TS(3, 8);
      } else if (warp == 10) {
        mbar_wait(sb + B_HFREE, 0);
        if (lane == 0) {
#pragma unroll 1
          for (int s = 0; s < 7; s++) {
            const int idx = (r * 9 + j) * 8 + ((j - 1 - s) & 7);
            wait_ge(&g_flag[idx], ep);
            asm volatile("fence.proxy.async.global;\n" ::: "memory");
            mbar_expect(sb + B_PFULL + 16 * s, 8192);
            bulk_g2s(sb + PS0 + s * 8192, g_part + (size_t)idx * 1024, 8192, sb + B_PFULL + 16 * s);
            mbar_expect(sb + B_PFULL + 16 * s + 8, 8192);
            bulk_g2s(sb + PS1 + s * 8192, g_part + (size_t)idx * 1024 + 512, 8192, sb + B_PFULL + 16 * s + 8);
          }
        }
        TS(3, 9);
      } else {
        if (lane < 8) wait_ge(&g_flag[(r * 9 + 8) * 8 + lane], ep);
        __syncwarp();
        const uint32_t* src = reinterpret_cast<const uint32_t*>(g_part + (size_t)(((r * 9 + 8) * 8) * 2 + (j >> 2)) * 512 + (j & 3) * 128) + lane;
        const int off0 = ((r * 128 + j * 16 + (lane >> 4) + 8 * (lane & 1)) * D_ + 512 + 8 * ((lane >> 1) & 1) + 2 * ((lane >> 2) & 3)) >> 1;
#pragma unroll 1
        for (int k = 0; k < 16; k++) {
          const int off = off0 + (k & 3) * D_ + (k >> 2) * 8;
          const uint32_t xv = __ldg(reinterpret_cast<const uint32_t*>(p.x) + off);
          uint32_t v[8];
#pragma unroll
          for (int jj = 0; jj < 8; jj++) v[jj] = __ldcg(src + k * 32 + jj * 4096);
          float s0 = blo(xv), s1 = bhi(xv);
#pragma unroll
          for (int jj = 0; jj < 8; jj++) { s0 += blo(v[jj]); s1 += bhi(v[jj]); }
          reinterpret_cast<uint32_t*>(p.out)[off] = pack2(s0, s1);
        }
        TS(3, 10);
        if (lane == 0) g_epoch[blockIdx.x] = ep;
      }
    }
  } else {
    asm volatile("setmaxnreg.inc.sync.aligned.u32 240;\n");
    const int wg = warp >> 2;
    uint32_t a[36][4];
    float dA[32], dB[32];
    const bool l0 = lane == 0;
    constexpr uint64_t dsw128 = mkdesc(sb, 16, 1024, 1);
    constexpr uint64_t dsw64 = mkdesc(sb, SLOT / 2, 512, 2);

    auto issue = [&](float (&d)[32], const uint64_t dbase, const int kstride, const int s, const uint32_t ph) {
      mbar_wait(sb + B_FULL + 8 * s, ph);
      wg_fence();
#pragma unroll
      for (int ks = 0; ks < 6; ks++) wgmma_rs64(d, a[s * 6 + ks], dbase + ((s * SLOT + ks * kstride) >> 4), (s | ks) != 0);
    };
    auto finish = [&](const int rel) {
      wg_commit();
      wg_wait<1>();
      if (rel >= 0 && l0) mbar_arrive(sb + B_EMPTY + 8 * rel);
    };
    auto stW = [&](float (&d)[32], const int s, const uint32_t ph, const int rel) { issue(d, dsw128, 2048, s, ph); finish(rel); };
    auto stF = [&](float (&d)[32], const int s, const uint32_t ph, const int rel) { issue(d, dsw64, 1024, s, ph); finish(rel); };

    TSC(1);
    uint32_t mb0, mb1;
    float r0, r1;
    {
      const uint32_t xa = sb + HB + (warp * 16 + (lane & 15)) * 128;
      const uint32_t sw = lane & 7, hi = lane >> 4;
      constexpr uint32_t ONES = 0x3F803F80u;
      float c[4][4];
      uint32_t pv0 = 0, pv1 = 0;
#pragma unroll
      for (int i = 0; i < 4; i++) { c[i][0] = c[i][1] = c[i][2] = c[i][3] = 0.f; }
#pragma unroll
      for (int b = 0; b < 9; b++) {
        mbar_wait(sb + B_X + 8 * b, 0);
#pragma unroll
        for (int kk = 0; kk < 4; kk++) ldsm4(a[4 * b + kk][0], a[4 * b + kk][1], a[4 * b + kk][2], a[4 * b + kk][3], xa + b * 16384 + (((2 * kk + hi) ^ sw) << 4));
        if (b == 0) {
          pv0 = __byte_perm(__shfl_sync(0xffffffffu, a[0][0], lane & ~3), 0, 0x1010);
          pv1 = __byte_perm(__shfl_sync(0xffffffffu, a[0][1], lane & ~3), 0, 0x1010);
        }
#pragma unroll
        for (int kk = 0; kk < 4; kk++) {
          const uint32_t e0 = bsub2(a[4 * b + kk][0], pv0), e2 = bsub2(a[4 * b + kk][2], pv0);
          const uint32_t e1 = bsub2(a[4 * b + kk][1], pv1), e3 = bsub2(a[4 * b + kk][3], pv1);
          mma16816(c[kk & 1], e0, ONES, e2, ONES, e0, e2);
          mma16816(c[2 + (kk & 1)], e1, ONES, e3, ONES, e1, e3);
        }
      }
      TSC(2);
      __syncwarp();
      if (l0) mbar_arrive(sb + B_XDONE);
      const bool godd = lane & 4;
      const int src = (lane & ~3) | (lane >> 3);
      const float s0 = __shfl_sync(0xffffffffu, godd ? c[0][3] + c[1][3] : c[0][2] + c[1][2], src) * (1.f / 576.f);
      const float s1 = __shfl_sync(0xffffffffu, godd ? c[2][3] + c[3][3] : c[2][2] + c[3][2], src) * (1.f / 576.f);
      const float q0 = __shfl_sync(0xffffffffu, godd ? c[0][1] + c[1][1] : c[0][0] + c[1][0], src) * (1.f / 576.f);
      const float q1 = __shfl_sync(0xffffffffu, godd ? c[2][1] + c[3][1] : c[2][0] + c[3][0], src) * (1.f / 576.f);
      const float m0 = blo(pv0) + s0, m1 = blo(pv1) + s1;
      mb0 = pack2(m0, m0);
      mb1 = pack2(m1, m1);
      r0 = rcp(rbf(sqrta(rbf(rbf(fmaxf(q0 - s0 * s0, 0.f)) + 1e-5f))));
      r1 = rcp(rbf(sqrta(rbf(rbf(fmaxf(q1 - s1 * s1, 0.f)) + 1e-5f))));
    }
    TSC(3);
    auto center = [&](const int g) {
#pragma unroll
      for (int ks = 6 * g; ks < 6 * g + 6; ks++) {
        a[ks][0] = bsub2(a[ks][0], mb0); a[ks][1] = bsub2(a[ks][1], mb1);
        a[ks][2] = bsub2(a[ks][2], mb0); a[ks][3] = bsub2(a[ks][3], mb1);
        asm volatile("" : "+r"(a[ks][0]), "+r"(a[ks][1]), "+r"(a[ks][2]), "+r"(a[ks][3])::"memory");
      }
    };
#pragma unroll
    for (int s = 0; s < 6; s++) {
      center(s);
      stW(dA, s, 0, s - 1);
    }
    TSC(4); GT(1);
    constexpr float LOG2E = 1.4426950408889634f;
    float l0e = r0 * LOG2E, l1e = r1 * LOG2E;
    const uint32_t tile_off = ((lane >> 4) + (j & 1)) * 2048 + (warp * 16 + (lane & 15)) * 16;
    mbar_wait(sb + B_XDONE, 0);
#pragma unroll
    for (int s = 0; s < 6; s++) {
      stW(dB, s, 1, (s + 5) % 6);
      if (s < 4) {
        const int t = 2 * s;
        pin8(dA, 4 * t);
        stsm4(sb + PK_T + tile_off + t * 2048, pack2(phi(dA[4 * t], r0, l0e), phi(dA[4 * t + 1], r0, l0e)), pack2(phi(dA[4 * t + 2], r1, l1e), phi(dA[4 * t + 3], r1, l1e)),
              pack2(phi(dA[4 * t + 4], r0, l0e), phi(dA[4 * t + 5], r0, l0e)), pack2(phi(dA[4 * t + 6], r1, l1e), phi(dA[4 * t + 7], r1, l1e)));
      }
    }
    TSC(5);
    {
#pragma unroll
      for (int s = 0; s < 2; s++) {
        stF(dA, s, 0, (s + 5) % 6);
#pragma unroll
        for (int t = 4 * s; t < 4 * s + 4; t += 2) {
          pin8(dB, 4 * t);
          stsm4(sb + V_T + tile_off + t * 2048, pack2(dB[4 * t] * r0, dB[4 * t + 1] * r0), pack2(dB[4 * t + 2] * r1, dB[4 * t + 3] * r1),
                pack2(dB[4 * t + 4] * r0, dB[4 * t + 5] * r0), pack2(dB[4 * t + 6] * r1, dB[4 * t + 7] * r1));
        }
      }
      float dL[12];
      constexpr uint64_t dl = mkdesc(sb + L24_T, 128, 576 * 16, 0);
      mbar_wait(sb + B_LFULL, 0);
#pragma unroll
      for (int s = 2; s < 5; s++) {
        mbar_wait(sb + B_FULL + 8 * s, 0);
        wg_fence();
#pragma unroll
        for (int ks = 12 * (s - 2); ks < 12 * (s - 1); ks++) wgmma_rs24(dL, a[ks], dl + ks * 16, ks != 0);
#pragma unroll
        for (int ks = 0; ks < 6; ks++) wgmma_rs64(dA, a[s * 6 + ks], dsw64 + ((s * SLOT + ks * 1024) >> 4), 1);
        finish(s - 1);
      }
      stF(dA, 5, 0, 4);
      pin(dL);
      const uint32_t lo = ((j & 1) ? 0 : 8 * 2048) + warp * 256 + lane * 4;
      sts32(sb + PK_T + lo, pack2(phi(dL[0], r0, l0e), phi(dL[1], r0, l0e)));
      sts32(sb + PK_T + lo + 128, pack2(phi(dL[2], r1, l1e), phi(dL[3], r1, l1e)));
      sts32(sb + V_T + lo, pack2(dL[4] * r0, dL[5] * r0));
      sts32(sb + V_T + lo + 128, pack2(dL[6] * r1, dL[7] * r1));
      sts64(sb + Q8 + tid * 8, pack2(dL[8], dL[9]), pack2(dL[10], dL[11]));
      fence_async_smem();
      __syncwarp();
      if (l0) mbar_arrive(sb + B_KVT);
    }
    TSC(6);
    uint32_t hs = sb + HB + wg * HHALF + (tid & 127) * 16;
    uint32_t hp0, hp1;
    const float iq0 = rcp(r0 * r0), iq1 = rcp(r1 * r1);
    auto epiF = [&](float (&d)[32], const int pc) {
      asm volatile("" : "+f"(d[4 * pc]), "+f"(d[4 * pc + 1]), "+f"(d[4 * pc + 2]), "+f"(d[4 * pc + 3]), "+f"(d[4 * pc + 16]), "+f"(d[4 * pc + 17]),
                   "+f"(d[4 * pc + 18]), "+f"(d[4 * pc + 19])::"memory");
      const float g0 = d[4 * pc], g1 = d[4 * pc + 1], g2 = d[4 * pc + 2], g3 = d[4 * pc + 3];
      const uint32_t h0 = pack2(g0 * d[4 * pc + 16] * rcp(fmaf(ex2(-g0 * l0e), iq0, iq0)), g1 * d[4 * pc + 17] * rcp(fmaf(ex2(-g1 * l0e), iq0, iq0)));
      const uint32_t h1 = pack2(g2 * d[4 * pc + 18] * rcp(fmaf(ex2(-g2 * l1e), iq1, iq1)), g3 * d[4 * pc + 19] * rcp(fmaf(ex2(-g3 * l1e), iq1, iq1)));
      if (pc & 1) {
        sts128(hs, hp0, hp1, h0, h1);
        hs += 2048;
      } else {
        hp0 = h0; hp1 = h1;
        asm volatile("" : "+r"(hp0), "+r"(hp1)::"memory");
      }
    };
    {
      stF(dB, 0, 1, 5);
      epiF(dA, 0); epiF(dA, 1);
      stF(dB, 1, 1, 0);
      epiF(dA, 2); epiF(dA, 3);
      float dK[20];
      const uint64_t ka = mkdesc(sb + V_T - 2048 + wg * 3 * 2048, 128, 2048, 0), kb = mkdesc(sb + PK_T + wg * 4 * 2048, 128, 2048, 0);
      mbar_wait(sb + B_KVT, 0);
      mbar_wait(sb + B_FULL + 8 * 2, 1);
      wg_fence();
#pragma unroll
      for (int ks = 0; ks < 8; ks++) wgmma_ss40tt(dK, ka + ks * 16, kb + ks * 16, ks != 0);
#pragma unroll
      for (int ks = 0; ks < 6; ks++) wgmma_rs64(dB, a[12 + ks], dsw64 + ((2 * SLOT + ks * 1024) >> 4), 1);
      finish(1);
      stF(dB, 3, 1, 2);
      pin(dK);
      float4* dst = g_kvp + (j * 16 + r) * 1280 + warp * 160 + lane;
#pragma unroll
      for (int t = 0; t < 5; t++) __stcg(dst + t * 32, make_float4(dK[4 * t], dK[4 * t + 1], dK[4 * t + 2], dK[4 * t + 3]));
      __syncwarp();
      if (l0) mbar_arrive(sb + B_KVD);
      stF(dB, 4, 1, 3);
    }
#pragma unroll 1
    for (int it = 0; it < 8; it++) {
      stF(dB, 5, 1, 4);
      stF(dA, 0, 0, 5);
#pragma unroll
      for (int s = 1; s < 5; s++) { epiF(dB, s - 1); stF(dA, s, 0, s - 1); }
      stF(dA, 5, 0, 4);
      stF(dB, 0, 1, 5);
#pragma unroll
      for (int s = 1; s < 5; s++) { epiF(dA, s - 1); stF(dB, s, 1, s - 1); }
      TSC(7 + it);
    }
    stF(dB, 5, 1, 4);
    TSC(15);
    const uint32_t hl = sb + HB + wg * HHALF + (tid & 127) * 16;
    auto reload = [&](const int g) {
#pragma unroll
      for (int ks = 6 * g; ks < 6 * g + 6; ks++) lds128(a[ks][0], a[ks][1], a[ks][2], a[ks][3], hl + ks * 2048);
    };
    stW(dA, 0, 0, 5);
#pragma unroll
    for (int s = 1; s < 6; s++) {
      if (s < 5) epiF(dB, s - 1);
      stW(dA, s, 0, s - 1);
      reload(s - 1);
    }
    const uint32_t ot = sb + (wg ? OT1 : OT0);
    const uint64_t do_a = mkdesc(ot, 128, 1280, 0);
    constexpr uint64_t do_b = mkdesc(sb + WO_SLOT, 16, 1024, 1);
    auto stO = [&](float (&d)[32], const uint32_t ph, const int rel) {
      mbar_wait(sb + B_FULL + 48, ph);
      wg_fence();
#pragma unroll
      for (int ks = 0; ks < 5; ks++) wgmma_ss64(d, do_a + ks * 16, do_b + ks * 128);
      finish(rel);
    };
    auto epiP = [&](float (&d)[32], const int step) {
      pin(d);
      const int c = step == 0 ? 8 : ((j + step) & 7);
      uint4* dst = g_part + (size_t)(((r * 9 + c) * 8 + j) * 2 + wg) * 512 + (warp & 3) * 128 + lane;
#pragma unroll
      for (int i = 0; i < 4; i++)
        __stcg(dst + i * 32, make_uint4(pack2(d[8 * i], d[8 * i + 1]), pack2(d[8 * i + 2], d[8 * i + 3]), pack2(d[8 * i + 4], d[8 * i + 5]), pack2(d[8 * i + 6], d[8 * i + 7])));
      __syncwarp();
      if (l0) mbar_arrive(sb + B_PUB + 8 * step);
    };
    TSC(16);
    {
      stW(dB, 0, 1, 5);
      reload(5);
      asm volatile("" : "+f"(l0e), "+f"(l1e));
      r0 = l0e * (1.f / LOG2E); r1 = l1e * (1.f / LOG2E);
      float pq[36];
      {
        uint32_t q0, q1;
        lds64(q0, q1, sb + Q8 + tid * 8);
        pin(dA);
        const float ql[4] = {blo(q0), bhi(q0), blo(q1), bhi(q1)};
        const bool odd = j & 1;
#pragma unroll
        for (int i = 0; i < 36; i++) {
          if (i < 4) pq[i] = odd ? ql[i] : dA[i];
          else if (i < 32) pq[i] = odd ? dA[i - 4] : dA[i];
          else pq[i] = odd ? dA[i - 4] : ql[i - 32];
        }
        pin(pq);
      }
      fence_async_smem();
      __syncwarp();
      if (l0) mbar_arrive(sb + B_HFREE);
      stW(dB, 1, 1, 0);
#pragma unroll
      for (int i = 0; i < 18; i++) pq[i] = (i & 2) ? phi(pq[i], r1, l1e) : phi(pq[i], r0, l0e);
      pin(pq);
      stW(dB, 2, 1, 1);
#pragma unroll
      for (int i = 18; i < 36; i++) pq[i] = (i & 2) ? phi(pq[i], r1, l1e) : phi(pq[i], r0, l0e);
      pin(pq);
      TSC(17);
      mbar_wait(sb + B_MRDY, 0);
      TSC(18);
      stW(dB, 3, 1, 2);
      const int q = lane & 3;
      float den[8];
#pragma unroll
      for (int i = 0; i < 8; i++) den[i] = 0.f;
#pragma unroll
      for (int t = 0; t < 9; t++) {
        uint32_t z0, z1;
        lds64(z0, z1, sb + ZS + t * 32 + q * 8);
        const float s0 = fmaf(pq[4 * t], __uint_as_float(z0), pq[4 * t + 1] * __uint_as_float(z1));
        const float s1 = fmaf(pq[4 * t + 2], __uint_as_float(z0), pq[4 * t + 3] * __uint_as_float(z1));
        const int lo = (8 * t) / 18, hi = (8 * t + 7) / 18;
        if (lo == hi) { den[2 * lo] += s0; den[2 * lo + 1] += s1; }
        else if (8 * t + 2 * q >= 18 * hi) { den[2 * hi] += s0; den[2 * hi + 1] += s1; }
        else { den[2 * lo] += s0; den[2 * lo + 1] += s1; }
      }
      pin(den);
      bar_sync(1 + wg, 128);
      stW(dB, 4, 1, 3);
#pragma unroll
      for (int i = 0; i < 8; i++) den[i] += __shfl_xor_sync(0xffffffffu, den[i], 1);
#pragma unroll
      for (int i = 0; i < 8; i++) den[i] = rcp(den[i] + __shfl_xor_sync(0xffffffffu, den[i], 2) + 1e-6f);
      const uint32_t oa = ot + ((warp & 3) * 2 + ((lane >> 3) & 1)) * 1280 + (lane >> 4) * 128 + (lane & 7) * 16;
#pragma unroll
      for (int t = 0; t < 10; t += 2) {
        uint32_t o[4];
#pragma unroll
        for (int z = 0; z < 2; z++) {
          const int tt = t + z;
          if (tt < 9) {
            const int lo = (8 * tt) / 18, hi = (8 * tt + 7) / 18;
            const bool up = lo != hi && 8 * tt + 2 * q >= 18 * hi;
            const float i0 = up ? den[2 * hi] : den[2 * lo], i1 = up ? den[2 * hi + 1] : den[2 * lo + 1];
            o[2 * z] = pack2(pq[4 * tt] * i0, pq[4 * tt + 1] * i0);
            o[2 * z + 1] = pack2(pq[4 * tt + 2] * i1, pq[4 * tt + 3] * i1);
          } else {
            o[2 * z] = 0; o[2 * z + 1] = 0;
          }
        }
        stsm4(oa + t * 128, o[0], o[1], o[2], o[3]);
      }
      fence_async_smem();
      stW(dB, 5, 1, 4);
      bar_sync(1 + wg, 128);
      stO(dB, 0, 5);
    }
    stW(dA, 0, 0, 6);
    epiP(dB, 0);
    TSC(19);
#pragma unroll 1
    for (int it = 0; it < 3; it++) {
#pragma unroll
      for (int s = 1; s < 6; s++) stW(dA, s, 0, s - 1);
      stO(dA, 1, 5);
      stW(dB, 0, 1, 6);
      epiP(dA, 1 + 2 * it);
#pragma unroll
      for (int s = 1; s < 6; s++) stW(dB, s, 1, s - 1);
      stO(dB, 0, 5);
      stW(dA, 0, 0, 6);
      epiP(dB, 2 + 2 * it);
      TSC(20 + it);
    }
#pragma unroll
    for (int s = 1; s < 6; s++) stW(dA, s, 0, s - 1);
    stO(dA, 1, 5);
    stW(dB, 0, 1, 6);
    epiP(dA, 7);
    TSC(23);
    {
      const __nv_bfloat16* xp = p.x + (size_t)(r * 128 + warp * 16 + (lane >> 2)) * D_ + 64 * j + 2 * (lane & 3);
      uint32_t xv[16];
#pragma unroll
      for (int t = 0; t < 8; t++) {
        xv[2 * t] = __ldg(reinterpret_cast<const uint32_t*>(xp + 8 * t));
        xv[2 * t + 1] = __ldg(reinterpret_cast<const uint32_t*>(xp + 8 * D_ + 8 * t));
      }
      stW(dB, 1, 1, -1);
      stW(dB, 2, 1, -1);
#pragma unroll
      for (int i = 0; i < 16; i++) { dA[2 * i] = blo(xv[i]); dA[2 * i + 1] = bhi(xv[i]); }
    }
    const uint32_t ps = sb + (wg ? PS1 : PS0) + (warp & 3) * 2048;
    auto addp = [&](const int s) {
      mbar_wait(sb + B_PFULL + 16 * s + 8 * wg, 0);
#pragma unroll
      for (int i = 0; i < 4; i++) {
        uint32_t v0, v1, v2, v3;
        lds128(v0, v1, v2, v3, ps + s * 8192 + i * 512 + lane * 16);
        dA[8 * i] += blo(v0); dA[8 * i + 1] += bhi(v0); dA[8 * i + 2] += blo(v1); dA[8 * i + 3] += bhi(v1);
        dA[8 * i + 4] += blo(v2); dA[8 * i + 5] += bhi(v2); dA[8 * i + 6] += blo(v3); dA[8 * i + 7] += bhi(v3);
      }
      pin(dA);
    };
    addp(0);
    stW(dB, 3, 1, -1);
    addp(1); addp(2);
    stW(dB, 4, 1, -1);
    addp(3); addp(4);
    stW(dB, 5, 1, -1);
    addp(5);
    stO(dB, 0, -1);
    TSC(24);
    addp(6);
    TSC(25);
    wg_wait<0>();
    TSC(26); GT(2);
    pin(dB);
    {
      __syncwarp();
      const int row = lane & 15;
#pragma unroll
      for (int t = 0; t < 8; t += 2)
        stsm4(ps + row * 128 + (((t + (lane >> 4)) ^ (row & 7)) << 4),
              pack2(dA[4 * t] + dB[4 * t], dA[4 * t + 1] + dB[4 * t + 1]), pack2(dA[4 * t + 2] + dB[4 * t + 2], dA[4 * t + 3] + dB[4 * t + 3]),
              pack2(dA[4 * t + 4] + dB[4 * t + 4], dA[4 * t + 5] + dB[4 * t + 5]), pack2(dA[4 * t + 6] + dB[4 * t + 6], dA[4 * t + 7] + dB[4 * t + 7]));
      __syncwarp();
#pragma unroll
      for (int i = 0; i < 4; i++) {
        const int rr = i * 4 + (lane >> 3), ch = lane & 7;
        uint4 v;
        lds128(v.x, v.y, v.z, v.w, ps + rr * 128 + ((ch ^ (rr & 7)) << 4));
        *reinterpret_cast<uint4*>(p.out + (size_t)(r * 128 + warp * 16 + rr) * D_ + 64 * j + ch * 8) = v;
      }
    }
    TSC(27); GT(3);
  }
}

typedef CUresult (*EncodeFn)(CUtensorMap*, CUtensorMapDataType, cuuint32_t, void*, const cuuint64_t*, const cuuint64_t*, const cuuint32_t*,
                             const cuuint32_t*, CUtensorMapInterleave, CUtensorMapSwizzle, CUtensorMapL2promotion, CUtensorMapFloatOOBfill);

CUtensorMap make_map(EncodeFn enc, const void* ptr, int rows, int cols, int brow, int bcol, CUtensorMapSwizzle sw) {
  CUtensorMap m;
  cuuint64_t gd[2] = {(cuuint64_t)cols, (cuuint64_t)rows};
  cuuint64_t gs[1] = {(cuuint64_t)cols * 2};
  cuuint32_t bd[2] = {(cuuint32_t)bcol, (cuuint32_t)brow};
  cuuint32_t es[2] = {1, 1};
  enc(&m, CU_TENSOR_MAP_DATA_TYPE_BFLOAT16, 2, const_cast<void*>(ptr), gd, gs, bd, es, CU_TENSOR_MAP_INTERLEAVE_NONE, sw,
      CU_TENSOR_MAP_L2_PROMOTION_L2_128B, CU_TENSOR_MAP_FLOAT_OOB_FILL_NONE);
  return m;
}

}

extern "C" void kernel_launch(void* const* d_in, const int* in_sizes, int n_in, void* d_out, int out_size) {
  (void)in_sizes; (void)n_in; (void)out_size;
  static EncodeFn enc = nullptr;
  static void* m_ptr = nullptr;
  if (!enc) {
    cudaGetSymbolAddress(&m_ptr, g_M);
    cudaDriverEntryPointQueryResult qr;
    cudaGetDriverEntryPoint("cuTensorMapEncodeTiled", (void**)&enc, cudaEnableDefault, &qr);
    cudaFuncSetAttribute(fused_block_kernel, cudaFuncAttributeMaxDynamicSharedMemorySize, SMEM_BYTES);
  }
  Params p;
  p.x = (const __nv_bfloat16*)d_in[0];
  p.wqkv = (const __nv_bfloat16*)d_in[1];
  p.wo = (const __nv_bfloat16*)d_in[2];
  p.w1 = (const __nv_bfloat16*)d_in[4];
  p.w3 = (const __nv_bfloat16*)d_in[5];
  p.w2 = (const __nv_bfloat16*)d_in[6];
  p.out = (__nv_bfloat16*)d_out;
  const CUtensorMap m_qkv = make_map(enc, p.wqkv, D_, 3 * D_, 96, 64, CU_TENSOR_MAP_SWIZZLE_128B);
  const CUtensorMap m_w1 = make_map(enc, p.w1, D_, F_, 96, 32, CU_TENSOR_MAP_SWIZZLE_64B);
  const CUtensorMap m_w3 = make_map(enc, p.w3, D_, F_, 96, 32, CU_TENSOR_MAP_SWIZZLE_64B);
  const CUtensorMap m_w2 = make_map(enc, p.w2, F_, D_, 96, 64, CU_TENSOR_MAP_SWIZZLE_128B);
  const CUtensorMap m_M = make_map(enc, m_ptr, 8 * 80, D_, 80, 64, CU_TENSOR_MAP_SWIZZLE_128B);
  const CUtensorMap m_x = make_map(enc, p.x, 2048, D_, 128, 64, CU_TENSOR_MAP_SWIZZLE_128B);
  fused_block_kernel<<<128, NTHREADS, SMEM_BYTES>>>(m_qkv, m_w1, m_w3, m_w2, m_M, m_x, p);
}
```

```cpp
#include <cuda_runtime.h>
#include <cuda.h>
#include <cuda_bf16.h>
#include <stdint.h>

namespace {

constexpr int D_ = 576, F_ = 4608;
constexpr int NTHREADS = 384;

constexpr uint32_t SLOT = 12288;
constexpr uint32_t HB = 6 * SLOT;
constexpr uint32_t HHALF = 73728;
constexpr uint32_t PK_T = HB + 45056;
constexpr uint32_t V_T = HB + HHALF + 18432;
constexpr uint32_t L24_T = HB + 16384;
constexpr uint32_t WO_SLOT = HB + 67584;
constexpr uint32_t OT0 = HB, OT1 = HB + 137216;
constexpr uint32_t ACC = 24576;
constexpr uint32_t STG = 49152;
constexpr uint32_t Q8 = HB + 2 * HHALF;
constexpr uint32_t WOB = Q8 + 2048;
constexpr uint32_t KVS = WOB + 5184;
constexpr uint32_t ZM = WOB;
constexpr uint32_t TAGW = KVS + 1440;
constexpr uint32_t BARS = TAGW + 32;
constexpr uint32_t SMEM_BYTES = BARS + 512;

constexpr uint32_t B_X = BARS;
constexpr uint32_t B_FULL = BARS + 8 * 9;
constexpr uint32_t B_EMPTY = BARS + 8 * 16;
constexpr uint32_t B_XDONE = BARS + 8 * 23;
constexpr uint32_t B_KVT = BARS + 8 * 24;
constexpr uint32_t B_KVD = BARS + 8 * 25;
constexpr uint32_t B_HFREE = BARS + 8 * 26;
constexpr uint32_t B_LFULL = BARS + 8 * 27;
constexpr uint32_t B_MRDY = BARS + 8 * 28;

constexpr uint32_t SPIN_LIMIT = 1u << 22;

__device__ uint4 g_part[16 * 9 * 8 * 1024];
__device__ float4 g_kvp[8 * 16 * 1280];
__device__ __align__(128) __nv_bfloat16 g_M[8 * 80 * 576];
__device__ __align__(16) float g_z[8 * 72];
__device__ uint32_t g_cnt1[8 * 32], g_cnt2[8 * 32];
__device__ uint32_t g_epoch[128];

#define TS(slot, i)
#define TSC(i)
#define GT(i)

__device__ __forceinline__ void wg_fence() { asm volatile("wgmma.fence.sync.aligned;\n" ::: "memory"); }
__device__ __forceinline__ void wg_commit() { asm volatile("wgmma.commit_group.sync.aligned;\n" ::: "memory"); }
template <int N> __device__ __forceinline__ void wg_wait() { asm volatile("wgmma.wait_group.sync.aligned %0;\n" ::"n"(N) : "memory"); }
__host__ __device__ constexpr uint64_t mkdesc(uint32_t addr, uint32_t lbo, uint32_t sbo, uint32_t sw) {
  return (uint64_t)((addr & 0x3FFFF) >> 4) | ((uint64_t)(lbo >> 4) << 16) | ((uint64_t)(sbo >> 4) << 32) | ((uint64_t)sw << 62);
}
__device__ __forceinline__ void mbar_init(uint32_t a, uint32_t c) { asm volatile("mbarrier.init.shared::cta.b64 [%0], %1;\n" ::"r"(a), "r"(c) : "memory"); }
__device__ __forceinline__ void mbar_expect(uint32_t a, uint32_t b) { asm volatile("mbarrier.arrive.expect_tx.shared::cta.b64 _, [%0], %1;\n" ::"r"(a), "r"(b) : "memory"); }
__device__ __forceinline__ void mbar_arrive(uint32_t a) { asm volatile("mbarrier.arrive.shared::cta.b64 _, [%0];\n" ::"r"(a) : "memory"); }
__device__ __forceinline__ void mbar_wait(uint32_t a, uint32_t ph) {
  asm volatile(
      "{\n.reg .pred p;\n.reg .u32 n;\n"
      "mov.u32 n, 0;\n"
      "LOOP:\n"
      "mbarrier.try_wait.parity.shared::cta.b64 p, [%0], %1;\n"
      "@p bra DONE;\n"
      "add.u32 n, n, 1;\n"
      "setp.gt.u32 p, n, %2;\n"
      "@p trap;\n"
      "bra LOOP;\n"
      "DONE:\n}\n" ::"r"(a), "r"(ph), "n"(SPIN_LIMIT) : "memory");
}
__device__ __forceinline__ void cp_async16(uint32_t dst, const void* src) {
  asm volatile("cp.async.cg.shared.global [%0], [%1], 16;\n" ::"r"(dst), "l"(src) : "memory");
}
__device__ __forceinline__ void tma2d(uint32_t dst, const CUtensorMap* m, int c0, int c1, uint32_t bar) {
  asm volatile("cp.async.bulk.tensor.2d.shared::cluster.global.mbarrier::complete_tx::bytes [%0], [%1, {%3, %4}], [%2];\n" ::"r"(dst), "l"(m), "r"(bar), "r"(c0), "r"(c1) : "memory");
}
__device__ __forceinline__ void tma2d_prefetch(const CUtensorMap* m, int c0, int c1) {
  asm volatile("cp.async.bulk.prefetch.tensor.2d.L2.global [%0, {%1, %2}];\n" ::"l"(m), "r"(c0), "r"(c1) : "memory");
}
__device__ __forceinline__ void fence_async_smem() { asm volatile("fence.proxy.async.shared::cta;\n" ::: "memory"); }
__device__ __forceinline__ void bar_sync(int id, int n) { asm volatile("bar.sync %0, %1;\n" ::"r"(id), "r"(n) : "memory"); }
__device__ __forceinline__ void ldsm4(uint32_t& r0, uint32_t& r1, uint32_t& r2, uint32_t& r3, uint32_t a) {
  asm volatile("ldmatrix.sync.aligned.m8n8.x4.shared.b16 {%0,%1,%2,%3}, [%4];\n" : "=r"(r0), "=r"(r1), "=r"(r2), "=r"(r3) : "r"(a) : "memory");
}
__device__ __forceinline__ void stsm4(uint32_t a, uint32_t r0, uint32_t r1, uint32_t r2, uint32_t r3) {
  asm volatile("stmatrix.sync.aligned.m8n8.x4.shared.b16 [%0], {%1,%2,%3,%4};\n" ::"r"(a), "r"(r0), "r"(r1), "r"(r2), "r"(r3) : "memory");
}
__device__ __forceinline__ void sts128(uint32_t a, uint32_t r0, uint32_t r1, uint32_t r2, uint32_t r3) {
  asm volatile("st.shared.v4.b32 [%0], {%1,%2,%3,%4};\n" ::"r"(a), "r"(r0), "r"(r1), "r"(r2), "r"(r3) : "memory");
}
__device__ __forceinline__ void lds128(uint32_t& r0, uint32_t& r1, uint32_t& r2, uint32_t& r3, uint32_t a) {
  asm volatile("ld.shared.v4.b32 {%0,%1,%2,%3}, [%4];\n" : "=r"(r0), "=r"(r1), "=r"(r2), "=r"(r3) : "r"(a) : "memory");
}
template <int OFF>
__device__ __forceinline__ void lds128_inplace(uint32_t (&r)[4], uint32_t a) {
  asm volatile("{\n.reg .pred p;\nsetp.ne.u32 p, %4, 0;\n@p ld.shared.v4.b32 {%0,%1,%2,%3}, [%4 + %5];\n}\n"
               : "+r"(r[0]), "+r"(r[1]), "+r"(r[2]), "+r"(r[3]) : "r"(a), "n"(OFF) : "memory");
}
__device__ __forceinline__ void sts64(uint32_t a, uint32_t r0, uint32_t r1) { asm volatile("st.shared.v2.b32 [%0], {%1,%2};\n" ::"r"(a), "r"(r0), "r"(r1) : "memory"); }
__device__ __forceinline__ void lds64(uint32_t& r0, uint32_t& r1, uint32_t a) { asm volatile("ld.shared.v2.b32 {%0,%1}, [%2];\n" : "=r"(r0), "=r"(r1) : "r"(a) : "memory"); }
__device__ __forceinline__ uint32_t lds32(uint32_t a) { uint32_t v; asm volatile("ld.shared.b32 %0, [%1];\n" : "=r"(v) : "r"(a) : "memory"); return v; }
__device__ __forceinline__ void sts32(uint32_t a, uint32_t r0) { asm volatile("st.shared.b32 [%0], %1;\n" ::"r"(a), "r"(r0) : "memory"); }
__device__ __forceinline__ void mma16816(float (&c)[4], uint32_t a0, uint32_t a1, uint32_t a2, uint32_t a3, uint32_t b0, uint32_t b1) {
  asm volatile("mma.sync.aligned.m16n8k16.row.col.f32.bf16.bf16.f32 {%0,%1,%2,%3}, {%4,%5,%6,%7}, {%8,%9}, {%0,%1,%2,%3};\n"
               : "+f"(c[0]), "+f"(c[1]), "+f"(c[2]), "+f"(c[3]) : "r"(a0), "r"(a1), "r"(a2), "r"(a3), "r"(b0), "r"(b1));
}
__device__ __forceinline__ uint32_t pack2(float lo, float hi) {
  uint32_t r;
  asm("cvt.rn.bf16x2.f32 %0, %1, %2;\n" : "=r"(r) : "f"(hi), "f"(lo));
  return r;
}
__device__ __forceinline__ float blo(uint32_t w) { return __uint_as_float(w << 16); }
__device__ __forceinline__ float bhi(uint32_t w) { return __uint_as_float(w & 0xffff0000u); }
__device__ __forceinline__ float rbf(float x) { return __bfloat162float(__float2bfloat16_rn(x)); }
__device__ __forceinline__ float ex2(float x) { float r; asm("ex2.approx.ftz.f32 %0, %1;\n" : "=f"(r) : "f"(x)); return r; }
__device__ __forceinline__ float rcp(float x) { float r; asm("rcp.approx.ftz.f32 %0, %1;\n" : "=f"(r) : "f"(x)); return r; }
__device__ __forceinline__ float sqrta(float x) { float r; asm("sqrt.approx.ftz.f32 %0, %1;\n" : "=f"(r) : "f"(x)); return r; }
__device__ __forceinline__ uint32_t bsub2(uint32_t a, uint32_t b) { uint32_t r; asm("sub.rn.bf16x2 %0, %1, %2;\n" : "=r"(r) : "r"(a), "r"(b)); return r; }
__device__ __forceinline__ uint32_t ld_acq(const uint32_t* p) { uint32_t v; asm volatile("ld.acquire.gpu.global.u32 %0, [%1];\n" : "=r"(v) : "l"(p) : "memory"); return v; }
__device__ __forceinline__ void st_b128(void* p, uint32_t a, uint32_t b, uint32_t c, uint32_t d) {
  asm volatile("{\n.reg .b128 v;\nmov.b128 v, {%1, %2, %3, %4};\nst.relaxed.gpu.global.b128 [%0], v;\n}\n" ::"l"(p), "r"(a), "r"(b), "r"(c), "r"(d) : "memory");
}
__device__ __forceinline__ void ld_b128(uint32_t& a, uint32_t& b, uint32_t& c, uint32_t& d, const void* p) {
  asm volatile("{\n.reg .b128 v;\nld.relaxed.gpu.global.b128 v, [%4];\nmov.b128 {%0, %1, %2, %3}, v;\n}\n" : "=r"(a), "=r"(b), "=r"(c), "=r"(d) : "l"(p) : "memory");
}
__device__ __forceinline__ bool elect_one() {
  uint32_t ok;
  asm volatile("{\n.reg .pred p;\nelect.sync _|p, 0xffffffff;\nselp.u32 %0, 1, 0, p;\n}\n" : "=r"(ok));
  return ok;
}
__device__ __forceinline__ uint32_t bmul2(uint32_t a, uint32_t b) { uint32_t r; asm("mul.rn.bf16x2 %0, %1, %2;\n" : "=r"(r) : "r"(a), "r"(b)); return r; }
__device__ __forceinline__ void red_rel(uint32_t* p) { asm volatile("red.release.gpu.global.add.u32 [%0], 1;\n" ::"l"(p) : "memory"); }
__device__ __forceinline__ void wait_ge(const uint32_t* p, uint32_t target) {
  uint32_t n = 0;
  while ((int32_t)(ld_acq(p) - target) < 0) {
    __nanosleep(64);
    if (++n > SPIN_LIMIT) __trap();
  }
}
__device__ __forceinline__ float phi(float a, float r, float rl) { return fmaf(fmaxf(a, 0.f), r, __saturatef(ex2(a * rl) + 1e-6f)); }

#define ACC8(d, o) "+f"(d[o + 0]), "+f"(d[o + 1]), "+f"(d[o + 2]), "+f"(d[o + 3]), "+f"(d[o + 4]), "+f"(d[o + 5]), "+f"(d[o + 6]), "+f"(d[o + 7])
#define REGS32 "{%0,%1,%2,%3,%4,%5,%6,%7,%8,%9,%10,%11,%12,%13,%14,%15,%16,%17,%18,%19,%20,%21,%22,%23,%24,%25,%26,%27,%28,%29,%30,%31}"
__device__ __forceinline__ void wgmma_rs64(float (&d)[32], const uint32_t (&a)[4], uint64_t db, int acc) {
  asm volatile("{\n.reg .pred p;\nsetp.ne.b32 p, %37, 0;\n"
               "wgmma.mma_async.sync.aligned.m64n64k16.f32.bf16.bf16 " REGS32 ", {%32,%33,%34,%35}, %36, p, 1, 1, 1;\n}\n"
               : ACC8(d, 0), ACC8(d, 8), ACC8(d, 16), ACC8(d, 24)
               : "r"(a[0]), "r"(a[1]), "r"(a[2]), "r"(a[3]), "l"(db), "r"(acc));
}
template <uint32_t OFF, uint32_t HI>
__device__ __forceinline__ void wgmma_ss64(float (&d)[32], uint32_t da_lo, uint64_t db) {
  asm volatile("{\n.reg .b32 lo;\n.reg .b64 da;\nadd.u32 lo, %32, %34;\nmov.b64 da, {lo, %35};\n"
               "wgmma.mma_async.sync.aligned.m64n64k16.f32.bf16.bf16 " REGS32 ", da, %33, 1, 1, 1, 0, 1;\n}\n"
               : ACC8(d, 0), ACC8(d, 8), ACC8(d, 16), ACC8(d, 24)
               : "r"(da_lo), "l"(db), "n"(OFF), "n"(HI));
}
__device__ __forceinline__ void wgmma_rs24(float (&d)[12], const uint32_t (&a)[4], uint64_t db, int acc) {
  asm volatile("{\n.reg .pred p;\nsetp.ne.b32 p, %17, 0;\n"
               "wgmma.mma_async.sync.aligned.m64n24k16.f32.bf16.bf16 {%0,%1,%2,%3,%4,%5,%6,%7,%8,%9,%10,%11}, {%12,%13,%14,%15}, %16, p, 1, 1, 1;\n}\n"
               : ACC8(d, 0), "+f"(d[8]), "+f"(d[9]), "+f"(d[10]), "+f"(d[11])
               : "r"(a[0]), "r"(a[1]), "r"(a[2]), "r"(a[3]), "l"(db), "r"(acc));
}
__device__ __forceinline__ void wgmma_ss40tt(float (&d)[20], uint64_t da, uint64_t db, int acc) {
  asm volatile("{\n.reg .pred p;\nsetp.ne.b32 p, %22, 0;\n"
               "wgmma.mma_async.sync.aligned.m64n40k16.f32.bf16.bf16 {%0,%1,%2,%3,%4,%5,%6,%7,%8,%9,%10,%11,%12,%13,%14,%15,%16,%17,%18,%19}, %20, %21, p, 1, 1, 1, 1;\n}\n"
               : ACC8(d, 0), ACC8(d, 8), "+f"(d[16]), "+f"(d[17]), "+f"(d[18]), "+f"(d[19])
               : "l"(da), "l"(db), "r"(acc));
}
template <uint32_t OFF, uint32_t HI, int ACCUM>
__device__ __forceinline__ void wgmma_ss16(float (&d)[8], uint32_t da_lo, uint64_t db) {
  asm volatile("{\n.reg .b32 lo;\n.reg .b64 da;\n.reg .pred p;\nsetp.ne.b32 p, %12, 0;\nadd.u32 lo, %8, %10;\nmov.b64 da, {lo, %11};\n"
               "wgmma.mma_async.sync.aligned.m64n16k16.f32.bf16.bf16 {%0,%1,%2,%3,%4,%5,%6,%7}, da, %9, p, 1, 1, 0, 1;\n}\n"
               : ACC8(d, 0)
               : "r"(da_lo), "l"(db), "n"(OFF), "n"(HI), "n"(ACCUM));
}
template <int N> __device__ __forceinline__ void pin(float (&d)[N]) {
#pragma unroll
  for (int i = 0; i < N; i++) asm volatile("" : "+f"(d[i])::"memory");
}

__device__ __forceinline__ void pin8(float (&d)[32], const int o) { asm volatile("" : ACC8(d, o)::"memory"); }

struct Params {
  const __nv_bfloat16* x;
  const __nv_bfloat16* wqkv;
  const __nv_bfloat16* wo;
  const __nv_bfloat16* w1;
  const __nv_bfloat16* w3;
  const __nv_bfloat16* w2;
  __nv_bfloat16* out;
};

__global__ void __launch_bounds__(NTHREADS, 1)
fused_block_kernel(const __grid_constant__ CUtensorMap m_qkv, const __grid_constant__ CUtensorMap m_w1,
                   const __grid_constant__ CUtensorMap m_w3, const __grid_constant__ CUtensorMap m_w2,
                   const __grid_constant__ CUtensorMap m_M, const __grid_constant__ CUtensorMap m_x, const Params p) {
  extern __shared__ __align__(1024) uint8_t smem_raw[];
  constexpr uint32_t sb = 1024;
  if ((uint32_t)__cvta_generic_to_shared(smem_raw) != sb) __trap();
  const int tid = threadIdx.x, warp = __shfl_sync(0xffffffffu, tid >> 5, 0), lane = tid & 31;
  const int r = blockIdx.x >> 3, j = blockIdx.x & 7;

  GT(0); TSC(0);
  const int cmain = 72 * j + 8 * (j & 1);
  if (warp == 8) {
    if (elect_one()) {
#pragma unroll
      for (int b = 0; b < 9; b++) mbar_init(sb + B_X + 8 * b, 1);
      asm volatile("fence.mbarrier_init.release.cluster;\n" ::: "memory");
#pragma unroll
      for (int b = 0; b < 9; b++) {
        mbar_expect(sb + B_X + 8 * b, 16384);
        tma2d(sb + HB + b * 16384, &m_x, 64 * b, 128 * r, sb + B_X + 8 * b);
      }
    }
  } else if (warp == 9) {
    if (elect_one()) {
      asm volatile("prefetch.tensormap [%0];\n" ::"l"(&m_qkv) : "memory");
#pragma unroll
      for (int i = 9; i < 29; i++) mbar_init(sb + BARS + 8 * i, i < 16 ? 1 : i < 27 ? 8 : 96);
      asm volatile("fence.mbarrier_init.release.cluster;\n" ::: "memory");
    }
  }
  __syncthreads();

  if (warp >= 8) {
    asm volatile("setmaxnreg.dec.sync.aligned.u32 24;\n");
    if (warp == 8) {
      if (elect_one()) {
#pragma unroll
        for (int s = 0; s < 6; s++) {
          mbar_expect(sb + B_FULL + 8 * s, SLOT);
          tma2d(sb + s * SLOT, &m_qkv, D_ + cmain, 96 * s, sb + B_FULL + 8 * s);
        }
        const CUtensorMap* mpf = (r & 1) ? &m_w3 : &m_w1;
        if (r < 6) tma2d_prefetch(&m_qkv, 2 * D_ + cmain, 96 * r);
        if (r < 12) { tma2d_prefetch(mpf, 576 * j, 96 * (r >> 1)); tma2d_prefetch(mpf, 576 * j + 32, 96 * (r >> 1)); }
#pragma unroll
        for (int s = 0; s < 6; s++) {
          mbar_wait(sb + B_EMPTY + 8 * s, 0);
          mbar_expect(sb + B_FULL + 8 * s, SLOT);
          tma2d(sb + s * SLOT, &m_qkv, 2 * D_ + cmain, 96 * s, sb + B_FULL + 8 * s);
        }
#pragma unroll 1
        for (int n = 0; n < 18; n++) {
          const int col = 576 * j + 32 * n;
          if (n < 16) { if (r < 12) tma2d_prefetch(mpf, col + 64, 96 * (r >> 1)); }
          else if (r < 6) {
            if (n == 16) tma2d_prefetch(&m_qkv, cmain, 96 * r);
            else tma2d_prefetch(&m_w2, 512, 576 * j + 96 * r);
          }
#pragma unroll
          for (int s = 0; s < 6; s++) {
            mbar_wait(sb + B_EMPTY + 8 * s, (n & 1) ^ 1);
            mbar_expect(sb + B_FULL + 8 * s, SLOT);
            tma2d(sb + s * SLOT, &m_w1, col, 96 * s, sb + B_FULL + 8 * s);
            tma2d(sb + s * SLOT + SLOT / 2, &m_w3, col, 96 * s, sb + B_FULL + 8 * s);
          }
        }
        if (r < 6) tma2d_prefetch(&m_w2, 64 * ((j + 1) & 7), 576 * j + 96 * r);
#pragma unroll
        for (int s = 0; s < 6; s++) {
          mbar_wait(sb + B_EMPTY + 8 * s, 1);
          mbar_expect(sb + B_FULL + 8 * s, SLOT);
          tma2d(sb + s * SLOT, &m_qkv, cmain, 96 * s, sb + B_FULL + 8 * s);
        }
#pragma unroll 1
        for (int n = 0; n < 9; n++) {
          const int col = n == 0 ? 512 : 64 * ((j + n) & 7);
          if (n < 7 && r < 6) tma2d_prefetch(&m_w2, 64 * ((j + n + 2) & 7), 576 * j + 96 * r);
#pragma unroll
          for (int s = 0; s < 6; s++) {
            mbar_wait(sb + B_EMPTY + 8 * s, n & 1);
            mbar_expect(sb + B_FULL + 8 * s, SLOT);
            tma2d(sb + s * SLOT, &m_w2, col, 576 * j + 96 * s, sb + B_FULL + 8 * s);
          }
          if (n == 0) {
            mbar_wait(sb + B_HFREE, 0);
            mbar_wait(sb + B_MRDY, 0);
            asm volatile("fence.proxy.async;\n" ::: "memory");
          }
          mbar_wait(sb + B_EMPTY + 48, (n & 1) ^ 1);
          mbar_expect(sb + B_FULL + 48, 80 * 128);
          tma2d(sb + WO_SLOT, &m_M, col, 80 * j, sb + B_FULL + 48);
        }
      }
    } else {
      const int ht = tid - 288;
      const uint32_t ep = g_epoch[blockIdx.x] + 1;
      mbar_wait(sb + B_X + 8 * 8, 0);
      if (ht < 90) {
        const int e = ht / 18, c = ht - e * 18;
        const __nv_bfloat16* w = p.wo + (size_t)(72 * j + 18 * (r >> 2) + e) * D_ + 144 * (r & 3) + c * 8;
#pragma unroll
        for (int i = 0; i < 4; i++)
          if (i < 3 || ht < 54) cp_async16(sb + WOB + ht * 16 + i * 90 * 16, w + i * 5 * D_);
      }
      const __nv_bfloat16* wl = p.wqkv + (size_t)ht * (3 * D_) + 72 * j + ((j & 1) ? 0 : 64);
      mbar_wait(sb + B_XDONE, 0);
#pragma unroll
      for (int g = 0; g < 3; g++)
#pragma unroll
        for (int m = 0; m < 6; m++) cp_async16(sb + L24_T + g * 9216 + m * 96 * 16 + ht * 16, wl + (size_t)m * 96 * 3 * D_ + (g == 2 ? 0 : (g + 1) * D_));
      if (ht < 64) {
#pragma unroll
        for (int i = 0; i < 4; i++) sts128(sb + V_T - 2048 + (i >> 1) * 20480 + (i & 1) * 1024 + ht * 16, 0x3F803F80u, 0x3F803F80u, 0x3F803F80u, 0x3F803F80u);
      }
      asm volatile("cp.async.wait_all;\n" ::: "memory");
      fence_async_smem();
      mbar_arrive(sb + B_LFULL);
      if (warp == 9) TS(3, 1);

      if (ht == 0) {
        mbar_wait(sb + B_KVD, 0);
        red_rel(&g_cnt1[j * 32]);
        wait_ge(&g_cnt1[j * 32], 16 * ep);
      }
      bar_sync(3, 96);
      if (warp == 9) TS(3, 4);
#pragma unroll 1
      for (int i = ht; i < 171; i += 96) {
        const int dp = i / 19, el = i - dp * 19, hd = r >> 2, w = hd >> 1;
        const int d = 18 * hd + 2 * dp - 32 * w;
        const int m = el == 18 ? 56 * w : 18 * hd + el + 8 - 24 * w;
        const float2* src = reinterpret_cast<const float2*>(g_kvp + j * 16 * 1280 + ((w * 4 + (m >> 4)) * 5 + (d >> 3)) * 32 + (m & 7) * 4 + ((d & 7) >> 1)) + ((m >> 3) & 1);
        float s0 = 0.f, s1 = 0.f;
#pragma unroll 1
        for (int r4 = 0; r4 < 4; r4++) {
          const float2 v0 = __ldcg(src), v1 = __ldcg(src + 2560), v2 = __ldcg(src + 2 * 2560), v3 = __ldcg(src + 3 * 2560);
          s0 += (v0.x + v1.x) + (v2.x + v3.x);
          s1 += (v0.y + v1.y) + (v2.y + v3.y);
          src += 4 * 2560;
        }
        sts64(sb + KVS + dp * 160 + el * 8, __float_as_uint(s0), __float_as_uint(s1));
        if ((r & 3) == 0 && el == 18) *reinterpret_cast<float2*>(g_z + j * 72 + hd * 18 + dp * 2) = make_float2(s0, s1);
      }
      bar_sync(3, 96);
      if (warp == 9) TS(3, 5);
#pragma unroll 1
      for (int t = ht; t < 648; t += 96) {
        const int dp = t / 72, cp = t - dp * 72;
        float c0 = 0.f, c1 = 0.f, c2 = 0.f, c3 = 0.f;
        const uint32_t ka = sb + KVS + dp * 160, wa = sb + WOB + cp * 4;
#pragma unroll
        for (int e2 = 0; e2 < 9; e2++) {
          uint32_t a0, a1, a2, a3;
          lds128(a0, a1, a2, a3, ka + e2 * 16);
          const uint32_t w0 = lds32(wa + e2 * 576), w1 = lds32(wa + e2 * 576 + 288);
          c0 = fmaf(__uint_as_float(a0), blo(w0), c0); c1 = fmaf(__uint_as_float(a0), bhi(w0), c1);
          c2 = fmaf(__uint_as_float(a1), blo(w0), c2); c3 = fmaf(__uint_as_float(a1), bhi(w0), c3);
          c0 = fmaf(__uint_as_float(a2), blo(w1), c0); c1 = fmaf(__uint_as_float(a2), bhi(w1), c1);
          c2 = fmaf(__uint_as_float(a3), blo(w1), c2); c3 = fmaf(__uint_as_float(a3), bhi(w1), c3);
        }
        const int d = 18 * (r >> 2) + 2 * dp;
        uint32_t* dst = reinterpret_cast<uint32_t*>(g_M) + (80 * j + ((j & 1) ? (d < 8 ? d + 64 : d - 8) : d)) * 288 + 72 * (r & 3) + cp;
        dst[0] = pack2(c0, c1);
        dst[288] = pack2(c2, c3);
      }
      asm volatile("fence.proxy.async;\n" ::: "memory");
      bar_sync(3, 96);
      if (warp == 9) TS(3, 6);
      if (ht == 0) { red_rel(&g_cnt2[j * 32]); wait_ge(&g_cnt2[j * 32], 16 * ep); }
      bar_sync(3, 96);
      if (ht < 80) {
        const int d = (j & 1) ? (ht < 64 ? ht + 8 : ht - 64) : ht;
        uint32_t zb = 0;
        if (ht < 72) zb = pack2(__ldcg(g_z + j * 72 + d), 0.f);
        const int hd = d / 18;
        const uint32_t w = (hd & 1) ? zb << 16 : zb;
        const uint32_t w0 = hd < 2 ? w : 0u, w1 = hd < 2 ? 0u : w;
        sts128(sb + ZM + ht * 16, w0, w0, w0, w0);
        sts128(sb + ZM + 1280 + ht * 16, w1, w1, w1, w1);
      }
      const uint32_t tag = (ep & 1) << 16;
      if (ht == 95) { sts32(sb + TAGW, tag); g_epoch[blockIdx.x] = ep; }
      fence_async_smem();
      mbar_arrive(sb + B_MRDY);
      if (warp == 9) TS(3, 7);
      if (warp < 11) {
        mbar_wait(sb + B_FULL + 48, 0);
#pragma unroll 1
        for (int i = warp - 9; i < 4; i += 2) {
          const uint4* src = g_part + (size_t)((r * 9 + 8) * 8) * 1024 + j * 128 + i * 32 + lane;
          const int off = ((r * 128 + j * 16 + (lane >> 2)) * D_ + 512 + 16 * i + 2 * (lane & 3)) >> 1;
          float s0, s1, s2, s3, s4, s5, s6, s7;
          {
            const uint32_t* xp = reinterpret_cast<const uint32_t*>(p.x) + off;
            const uint32_t x0 = __ldg(xp), x1 = __ldg(xp + 4 * D_), x2 = __ldg(xp + 4), x3 = __ldg(xp + 4 * D_ + 4);
            s0 = blo(x0); s1 = bhi(x0); s2 = blo(x1); s3 = bhi(x1); s4 = blo(x2); s5 = bhi(x2); s6 = blo(x3); s7 = bhi(x3);
          }
          uint32_t n = 0;
#pragma unroll 1
          for (int jj = 0; jj < 8;) {
            uint32_t v0, v1, v2, v3;
            ld_b128(v0, v1, v2, v3, src);
            if (__all_sync(0xffffffffu, ((v0 ^ tag) & 0x10000u) == 0)) {
              s0 += blo(v0); s1 += __uint_as_float(v0 & 0xfffe0000u); s2 += blo(v1); s3 += bhi(v1);
              s4 += blo(v2); s5 += bhi(v2); s6 += blo(v3); s7 += bhi(v3);
              jj++;
              src += 1024;
            } else {
              __nanosleep(200);
              if (++n > SPIN_LIMIT) __trap();
            }
          }
          uint32_t* op = reinterpret_cast<uint32_t*>(p.out) + off;
          op[0] = pack2(s0, s1); op[4 * D_] = pack2(s2, s3); op[4] = pack2(s4, s5); op[4 * D_ + 4] = pack2(s6, s7);
        }
        if (warp == 9) TS(3, 10);
      }
    }
  } else {
    asm volatile("setmaxnreg.inc.sync.aligned.u32 240;\n");
    const int wg = warp >> 2;
    uint32_t a[36][4];
    float dA[32], dB[32];
    const bool l0 = lane == 0;
    constexpr uint64_t dsw128 = mkdesc(sb, 16, 1024, 1);
    constexpr uint64_t dsw64 = mkdesc(sb, SLOT / 2, 512, 2);

    auto issue = [&](float (&d)[32], const uint64_t dbase, const int kstride, const int s, const uint32_t ph) {
      mbar_wait(sb + B_FULL + 8 * s, ph);
      wg_fence();
#pragma unroll
      for (int ks = 0; ks < 6; ks++) wgmma_rs64(d, a[s * 6 + ks], dbase + ((s * SLOT + ks * kstride) >> 4), (s | ks) != 0);
    };
    auto finish = [&](const int rel) {
      wg_commit();
      wg_wait<1>();
      if (rel >= 0 && l0) mbar_arrive(sb + B_EMPTY + 8 * rel);
    };
    auto stW = [&](float (&d)[32], const int s, const uint32_t ph, const int rel) { issue(d, dsw128, 2048, s, ph); finish(rel); };
    auto stF = [&](float (&d)[32], const int s, const uint32_t ph, const int rel) { issue(d, dsw64, 1024, s, ph); finish(rel); };

    TSC(1);
    uint32_t mb0, mb1;
    float r0, r1;
    {
      const uint32_t xa = sb + HB + (warp * 16 + (lane & 15)) * 128;
      const uint32_t sw = lane & 7, hi = lane >> 4;
      constexpr uint32_t ONES = 0x3F803F80u;
      float c[4][4];
#pragma unroll
      for (int i = 0; i < 4; i++) { c[i][0] = c[i][1] = c[i][2] = c[i][3] = 0.f; }
#pragma unroll
      for (int b = 0; b < 9; b++) {
        mbar_wait(sb + B_X + 8 * b, 0);
        if (b == 0 || b == 8) TSC(32 + b);
#pragma unroll
        for (int kk = 0; kk < 4; kk++) ldsm4(a[4 * b + kk][0], a[4 * b + kk][1], a[4 * b + kk][2], a[4 * b + kk][3], xa + b * 16384 + (((2 * kk + hi) ^ sw) << 4));
#pragma unroll
        for (int kk = 0; kk < 4; kk++) {
          const uint32_t(&e)[4] = a[4 * b + kk];
          mma16816(c[kk & 1], e[0], ONES, e[2], ONES, e[0], e[2]);
          mma16816(c[2 + (kk & 1)], e[1], ONES, e[3], ONES, e[1], e[3]);
        }
      }
      TSC(2);
      __syncwarp();
      if (l0) mbar_arrive(sb + B_XDONE);
      const bool godd = lane & 4;
      const int src = (lane & ~3) | (lane >> 3);
      const float m0 = __shfl_sync(0xffffffffu, godd ? c[0][3] + c[1][3] : c[0][2] + c[1][2], src) * (1.f / 576.f);
      const float m1 = __shfl_sync(0xffffffffu, godd ? c[2][3] + c[3][3] : c[2][2] + c[3][2], src) * (1.f / 576.f);
      const float q0 = __shfl_sync(0xffffffffu, godd ? c[0][1] + c[1][1] : c[0][0] + c[1][0], src) * (1.f / 576.f);
      const float q1 = __shfl_sync(0xffffffffu, godd ? c[2][1] + c[3][1] : c[2][0] + c[3][0], src) * (1.f / 576.f);
      mb0 = pack2(m0, m0);
      mb1 = pack2(m1, m1);
      float v0 = q0 - m0 * m0, v1 = q1 - m1 * m1;
      if (__any_sync(0xffffffffu, v0 < q0 * (1.f / 64.f) || v1 < q1 * (1.f / 64.f))) {
#pragma unroll
        for (int i = 0; i < 4; i++) { c[0][i] = 0.f; c[2][i] = 0.f; }
#pragma unroll
        for (int ks = 0; ks < 36; ks++) {
          const uint32_t e0 = bsub2(a[ks][0], mb0), e2 = bsub2(a[ks][2], mb0), e1 = bsub2(a[ks][1], mb1), e3 = bsub2(a[ks][3], mb1);
          mma16816(c[0], e0, ONES, e2, ONES, e0, e2);
          mma16816(c[2], e1, ONES, e3, ONES, e1, e3);
        }
        const float d0 = __shfl_sync(0xffffffffu, godd ? c[0][3] : c[0][2], src) * (1.f / 576.f);
        const float d1 = __shfl_sync(0xffffffffu, godd ? c[2][3] : c[2][2], src) * (1.f / 576.f);
        v0 = __shfl_sync(0xffffffffu, godd ? c[0][1] : c[0][0], src) * (1.f / 576.f) - d0 * d0;
        v1 = __shfl_sync(0xffffffffu, godd ? c[2][1] : c[2][0], src) * (1.f / 576.f) - d1 * d1;
      }
      r0 = rcp(rbf(sqrta(rbf(rbf(fmaxf(v0, 0.f)) + 1e-5f))));
      r1 = rcp(rbf(sqrta(rbf(rbf(fmaxf(v1, 0.f)) + 1e-5f))));
    }
    TSC(3);
    auto center = [&](const int g) {
#pragma unroll
      for (int ks = 6 * g; ks < 6 * g + 6; ks++) {
        a[ks][0] = bsub2(a[ks][0], mb0); a[ks][1] = bsub2(a[ks][1], mb1);
        a[ks][2] = bsub2(a[ks][2], mb0); a[ks][3] = bsub2(a[ks][3], mb1);
        asm volatile("" : "+r"(a[ks][0]), "+r"(a[ks][1]), "+r"(a[ks][2]), "+r"(a[ks][3])::"memory");
      }
    };
#pragma unroll
    for (int s = 0; s < 6; s++) {
      center(s);
      stW(dA, s, 0, s - 1);
    }
    TSC(4); GT(1);
    constexpr float LOG2E = 1.4426950408889634f;
    float l0e = r0 * LOG2E, l1e = r1 * LOG2E;
    const uint32_t tile_off = ((lane >> 4) + (j & 1)) * 2048 + (warp * 16 + (lane & 15)) * 16;
    mbar_wait(sb + B_XDONE, 0);
#pragma unroll
    for (int s = 0; s < 6; s++) {
      stW(dB, s, 1, (s + 5) % 6);
      if (s < 4) {
        const int t = 2 * s;
        pin8(dA, 4 * t);
        stsm4(sb + PK_T + tile_off + t * 2048, pack2(phi(dA[4 * t], r0, l0e), phi(dA[4 * t + 1], r0, l0e)), pack2(phi(dA[4 * t + 2], r1, l1e), phi(dA[4 * t + 3], r1, l1e)),
              pack2(phi(dA[4 * t + 4], r0, l0e), phi(dA[4 * t + 5], r0, l0e)), pack2(phi(dA[4 * t + 6], r1, l1e), phi(dA[4 * t + 7], r1, l1e)));
      }
    }
    TSC(5);
    {
#pragma unroll
      for (int s = 0; s < 2; s++) {
        stF(dA, s, 0, (s + 5) % 6);
#pragma unroll
        for (int t = 4 * s; t < 4 * s + 4; t += 2) {
          pin8(dB, 4 * t);
          stsm4(sb + V_T + tile_off + t * 2048, pack2(dB[4 * t] * r0, dB[4 * t + 1] * r0), pack2(dB[4 * t + 2] * r1, dB[4 * t + 3] * r1),
                pack2(dB[4 * t + 4] * r0, dB[4 * t + 5] * r0), pack2(dB[4 * t + 6] * r1, dB[4 * t + 7] * r1));
        }
      }
      float dL[12];
      constexpr uint64_t dl = mkdesc(sb + L24_T, 128, 576 * 16, 0);
      mbar_wait(sb + B_LFULL, 0);
#pragma unroll
      for (int s = 2; s < 5; s++) {
        mbar_wait(sb + B_FULL + 8 * s, 0);
        wg_fence();
#pragma unroll
        for (int ks = 12 * (s - 2); ks < 12 * (s - 1); ks++) wgmma_rs24(dL, a[ks], dl + ks * 16, ks != 0);
#pragma unroll
        for (int ks = 0; ks < 6; ks++) wgmma_rs64(dA, a[s * 6 + ks], dsw64 + ((s * SLOT + ks * 1024) >> 4), 1);
        finish(s - 1);
      }
      stF(dA, 5, 0, 4);
      pin(dL);
      const uint32_t lo = ((j & 1) ? 0 : 8 * 2048) + warp * 256 + lane * 4;
      sts32(sb + PK_T + lo, pack2(phi(dL[0], r0, l0e), phi(dL[1], r0, l0e)));
      sts32(sb + PK_T + lo + 128, pack2(phi(dL[2], r1, l1e), phi(dL[3], r1, l1e)));
      sts32(sb + V_T + lo, pack2(dL[4] * r0, dL[5] * r0));
      sts32(sb + V_T + lo + 128, pack2(dL[6] * r1, dL[7] * r1));
      sts64(sb + Q8 + tid * 8, pack2(dL[8], dL[9]), pack2(dL[10], dL[11]));
      fence_async_smem();
      __syncwarp();
      if (l0) mbar_arrive(sb + B_KVT);
    }
    TSC(6);
    uint32_t hs = sb + HB + wg * HHALF + (tid & 127) * 16;
    uint32_t hp0, hp1;
    const float iq0 = rcp(r0 * r0), iq1 = rcp(r1 * r1);
    auto epiF = [&](float (&d)[32], const int pc) {
      asm volatile("" : "+f"(d[4 * pc]), "+f"(d[4 * pc + 1]), "+f"(d[4 * pc + 2]), "+f"(d[4 * pc + 3]), "+f"(d[4 * pc + 16]), "+f"(d[4 * pc + 17]),
                   "+f"(d[4 * pc + 18]), "+f"(d[4 * pc + 19])::"memory");
      const float g0 = d[4 * pc], g1 = d[4 * pc + 1], g2 = d[4 * pc + 2], g3 = d[4 * pc + 3];
      const uint32_t h0 = pack2(g0 * d[4 * pc + 16] * rcp(fmaf(ex2(-g0 * l0e), iq0, iq0)), g1 * d[4 * pc + 17] * rcp(fmaf(ex2(-g1 * l0e), iq0, iq0)));
      const uint32_t h1 = pack2(g2 * d[4 * pc + 18] * rcp(fmaf(ex2(-g2 * l1e), iq1, iq1)), g3 * d[4 * pc + 19] * rcp(fmaf(ex2(-g3 * l1e), iq1, iq1)));
      if (pc & 1) {
        sts128(hs, hp0, hp1, h0, h1);
        hs += 2048;
      } else {
        hp0 = h0; hp1 = h1;
        asm volatile("" : "+r"(hp0), "+r"(hp1)::"memory");
      }
    };
    {
      stF(dB, 0, 1, 5);
      epiF(dA, 0); epiF(dA, 1);
      stF(dB, 1, 1, 0);
      epiF(dA, 2); epiF(dA, 3);
      float dK[20];
      const uint64_t ka = mkdesc(sb + V_T - 2048 + wg * 3 * 2048, 128, 2048, 0), kb = mkdesc(sb + PK_T + wg * 4 * 2048, 128, 2048, 0);
      mbar_wait(sb + B_KVT, 0);
      mbar_wait(sb + B_FULL + 8 * 2, 1);
      wg_fence();
#pragma unroll
      for (int ks = 0; ks < 8; ks++) wgmma_ss40tt(dK, ka + ks * 16, kb + ks * 16, ks != 0);
#pragma unroll
      for (int ks = 0; ks < 6; ks++) wgmma_rs64(dB, a[12 + ks], dsw64 + ((2 * SLOT + ks * 1024) >> 4), 1);
      finish(1);
      stF(dB, 3, 1, 2);
      pin(dK);
      float4* dst = g_kvp + (j * 16 + r) * 1280 + warp * 160 + lane;
#pragma unroll
      for (int t = 0; t < 5; t++) __stcg(dst + t * 32, make_float4(dK[4 * t], dK[4 * t + 1], dK[4 * t + 2], dK[4 * t + 3]));
      __syncwarp();
      if (l0) mbar_arrive(sb + B_KVD);
      stF(dB, 4, 1, 3);
    }
#pragma unroll 1
    for (int it = 0; it < 8; it++) {
      stF(dB, 5, 1, 4);
      stF(dA, 0, 0, 5);
#pragma unroll
      for (int s = 1; s < 5; s++) { epiF(dB, s - 1); stF(dA, s, 0, s - 1); }
      stF(dA, 5, 0, 4);
      stF(dB, 0, 1, 5);
#pragma unroll
      for (int s = 1; s < 5; s++) { epiF(dA, s - 1); stF(dB, s, 1, s - 1); }
      TSC(7 + it);
    }
    stF(dB, 5, 1, 4);
    TSC(15);
    const uint32_t hl = sb + HB + wg * HHALF + (tid & 127) * 16;
    auto reload = [&](const int g) {
      const uint32_t ha = hl + g * 12288;
      lds128_inplace<0>(a[6 * g], ha); lds128_inplace<2048>(a[6 * g + 1], ha); lds128_inplace<4096>(a[6 * g + 2], ha);
      lds128_inplace<6144>(a[6 * g + 3], ha); lds128_inplace<8192>(a[6 * g + 4], ha); lds128_inplace<10240>(a[6 * g + 5], ha);
    };
    stW(dA, 0, 0, 5);
#pragma unroll
    for (int s = 1; s < 6; s++) {
      if (s < 5) epiF(dB, s - 1);
      stW(dA, s, 0, s - 1);
      reload(s - 1);
    }
    const uint32_t ot = sb + (wg ? OT1 : OT0);
    const uint32_t do_a = (uint32_t)mkdesc(ot, 128, 1280, 0);
    constexpr uint64_t do_b = mkdesc(sb + WO_SLOT, 16, 1024, 1);
    auto stO = [&](float (&d)[32], const uint32_t ph, const int rel) {
      mbar_wait(sb + B_FULL + 48, ph);
      wg_fence();
      wgmma_ss64<0, 80>(d, do_a, do_b);
      wgmma_ss64<16, 80>(d, do_a, do_b + 128);
      wgmma_ss64<32, 80>(d, do_a, do_b + 256);
      wgmma_ss64<48, 80>(d, do_a, do_b + 384);
      wgmma_ss64<64, 80>(d, do_a, do_b + 512);
      finish(rel);
    };
    uint32_t tag;
    auto epiP = [&](float (&d)[32], const int step) {
      pin(d);
      const int c = step == 0 ? 8 : ((j + step) & 7);
      uint4* dst = g_part + (size_t)((r * 9 + c) * 8 + j) * 1024 + warp * 128 + lane;
#pragma unroll
      for (int i = 0; i < 4; i++)
        st_b128(dst + i * 32, (pack2(d[8 * i], d[8 * i + 1]) & 0xfffeffffu) | tag, pack2(d[8 * i + 2], d[8 * i + 3]), pack2(d[8 * i + 4], d[8 * i + 5]), pack2(d[8 * i + 6], d[8 * i + 7]));
    };
    TSC(16);
    {
      stW(dB, 0, 1, 5);
      reload(5);
      asm volatile("" : "+f"(l0e), "+f"(l1e));
      r0 = l0e * (1.f / LOG2E); r1 = l1e * (1.f / LOG2E);
      uint32_t pq[18];
      fence_async_smem();
      __syncwarp();
      if (l0) mbar_arrive(sb + B_HFREE);
      const uint32_t oa = ot + ((warp & 3) * 2 + ((lane >> 3) & 1)) * 1280 + (lane >> 4) * 128 + (lane & 7) * 16;
      auto phiq = [&](const int t0, const int t1) {
#pragma unroll
        for (int t = t0; t < t1; t++) {
          asm volatile("" : "+f"(dA[4 * t]), "+f"(dA[4 * t + 1]), "+f"(dA[4 * t + 2]), "+f"(dA[4 * t + 3])::"memory");
          pq[2 * t] = pack2(phi(dA[4 * t], r0, l0e), phi(dA[4 * t + 1], r0, l0e));
          pq[2 * t + 1] = pack2(phi(dA[4 * t + 2], r1, l1e), phi(dA[4 * t + 3], r1, l1e));
          asm volatile("" : "+r"(pq[2 * t]), "+r"(pq[2 * t + 1])::"memory");
        }
      };
      phiq(0, 3);
      stW(dB, 1, 1, 0);
      phiq(3, 6);
      bar_sync(1 + wg, 128);
      stW(dB, 2, 1, 1);
      phiq(6, 8);
      {
        uint32_t q0, q1;
        lds64(q0, q1, sb + Q8 + tid * 8);
        pq[16] = pack2(phi(blo(q0), r0, l0e), phi(bhi(q0), r0, l0e));
        pq[17] = pack2(phi(blo(q1), r1, l1e), phi(bhi(q1), r1, l1e));
      }
#pragma unroll
      for (int t = 0; t < 8; t += 2) stsm4(oa + t * 128, pq[2 * t], pq[2 * t + 1], pq[2 * t + 2], pq[2 * t + 3]);
      stsm4(oa + 1024, pq[16], pq[17], 0u, 0u);
      fence_async_smem();
      TSC(17);
      mbar_wait(sb + B_MRDY, 0);
      TSC(18);
      tag = lds32(sb + TAGW);
      float den[8];
      constexpr uint64_t dz = mkdesc(sb + ZM, 128, 1280, 0);
      bar_sync(1 + wg, 128);
      issue(dB, dsw128, 2048, 3, 1);
      wgmma_ss16<0, 80, 0>(den, do_a, dz);
      wgmma_ss16<16, 80, 1>(den, do_a, dz + 16);
      wgmma_ss16<32, 80, 1>(den, do_a, dz + 32);
      wgmma_ss16<48, 80, 1>(den, do_a, dz + 48);
      wgmma_ss16<64, 80, 1>(den, do_a, dz + 64);
      finish(2);
      stW(dB, 4, 1, 3);
      pin(den);
      uint32_t iv[8];
#pragma unroll
      for (int i = 0; i < 8; i++) { const float t = rcp(den[i] + 1e-6f); iv[i] = pack2(t, t); }
      const int u = 2 * (lane & 3) + 8 * (j & 1);
#pragma unroll
      for (int t = 0; t < 10; t += 2) {
        uint32_t o[4];
#pragma unroll
        for (int z = 0; z < 2; z++) {
          const int tt = t + z;
          if (tt < 9) {
            const int lo = tt == 0 ? 0 : tt >= 7 ? 3 : (tt - 1) >> 1, hi = tt == 8 ? 0 : (tt == 0 || tt == 7) ? lo : lo + 1;
            const bool up = tt == 8 ? (j & 1) : 8 * tt + u >= 18 * hi;
            const int il = (lo >> 1) * 4 + (lo & 1), ih = (hi >> 1) * 4 + (hi & 1);
            o[2 * z] = bmul2(pq[2 * tt], up ? iv[ih] : iv[il]);
            o[2 * z + 1] = bmul2(pq[2 * tt + 1], up ? iv[ih + 2] : iv[il + 2]);
          } else {
            o[2 * z] = 0; o[2 * z + 1] = 0;
          }
        }
        stsm4(oa + t * 128, o[0], o[1], o[2], o[3]);
      }
      fence_async_smem();
      stW(dB, 5, 1, 4);
      bar_sync(1 + wg, 128);
      stO(dB, 0, 5);
    }
    stW(dA, 0, 0, 6);
    epiP(dB, 0);
    TSC(19);
    auto ldp = [&](uint32_t (&v)[16], const int s) {
      const uint4* src = g_part + (size_t)((r * 9 + j) * 8 + ((j - 1 - s) & 7)) * 1024 + warp * 128 + lane;
#pragma unroll
      for (int i = 0; i < 4; i++) ld_b128(v[4 * i], v[4 * i + 1], v[4 * i + 2], v[4 * i + 3], src + i * 32);
    };
    auto chk = [&](uint32_t (&v)[16], const int s) {
      uint32_t n = 0;
      while (__any_sync(0xffffffffu, (((v[0] ^ tag) | (v[4] ^ tag) | (v[8] ^ tag) | (v[12] ^ tag)) & 0x10000u) != 0)) {
        ldp(v, s);
        if (++n > SPIN_LIMIT) asm volatile("trap;");
      }
    };
    const uint32_t acc = hl + ACC;
    auto accp = [&](uint32_t (&v)[16], const int i, const uint32_t hm) {
      uint32_t f[8];
      lds128(f[0], f[1], f[2], f[3], acc + i * 4096);
      lds128(f[4], f[5], f[6], f[7], acc + i * 4096 + 2048);
      auto U = [](float x) { return __float_as_uint(x); };
      auto F = [](uint32_t x) { return __uint_as_float(x); };
      sts128(acc + i * 4096, U(F(f[0]) + blo(v[4 * i])), U(F(f[1]) + F(v[4 * i] & hm)), U(F(f[2]) + blo(v[4 * i + 1])), U(F(f[3]) + bhi(v[4 * i + 1])));
      sts128(acc + i * 4096 + 2048, U(F(f[4]) + blo(v[4 * i + 2])), U(F(f[5]) + bhi(v[4 * i + 2])), U(F(f[6]) + blo(v[4 * i + 3])), U(F(f[7]) + bhi(v[4 * i + 3])));
    };
#pragma unroll 1
    for (int it = 0; it < 3; it++) {
      uint32_t v[16];
      if (it > 0) ldp(v, 2 * it - 2);
      else {
#pragma unroll
        for (int i = 0; i < 8; i++) sts128(acc + i * 2048, 0, 0, 0, 0);
      }
      stW(dA, 1, 0, 0);
      stW(dA, 2, 0, 1);
      stW(dA, 3, 0, 2);
      if (it > 0) { chk(v, 2 * it - 2); accp(v, 0, 0xfffe0000u); }
      stW(dA, 4, 0, 3);
      if (it > 0) accp(v, 1, 0xfffe0000u);
      stW(dA, 5, 0, 4);
      if (it > 0) accp(v, 2, 0xfffe0000u);
      stO(dA, 1, 5);
      if (it > 0) accp(v, 3, 0xfffe0000u);
      stW(dB, 0, 1, 6);
      epiP(dA, 1 + 2 * it);
      if (it > 0) ldp(v, 2 * it - 1);
      else {
        const uint32_t* xp = reinterpret_cast<const uint32_t*>(p.x + (size_t)(r * 128 + warp * 16 + (lane >> 2)) * D_ + 64 * j + 2 * (lane & 3));
#pragma unroll
        for (int t = 0; t < 8; t++) { v[2 * t] = __ldg(xp + 4 * t); v[2 * t + 1] = __ldg(xp + 4 * D_ + 4 * t); }
      }
      const uint32_t hm = it > 0 ? 0xfffe0000u : 0xffff0000u;
      stW(dB, 1, 1, 0);
      stW(dB, 2, 1, 1);
      stW(dB, 3, 1, 2);
      if (it > 0) chk(v, 2 * it - 1);
      accp(v, 0, hm);
      stW(dB, 4, 1, 3);
      accp(v, 1, hm);
      stW(dB, 5, 1, 4);
      accp(v, 2, hm);
      stO(dB, 0, 5);
      accp(v, 3, hm);
      stW(dA, 0, 0, 6);
      epiP(dB, 2 + 2 * it);
      TSC(20 + it);
    }
    {
      uint32_t v[16];
      ldp(v, 4);
      stW(dA, 1, 0, 0);
      stW(dA, 2, 0, 1);
      stW(dA, 3, 0, 2);
      chk(v, 4); accp(v, 0, 0xfffe0000u);
      stW(dA, 4, 0, 3);
      accp(v, 1, 0xfffe0000u);
      stW(dA, 5, 0, 4);
      accp(v, 2, 0xfffe0000u);
      stO(dA, 1, 5);
      accp(v, 3, 0xfffe0000u);
    }
    stW(dB, 0, 1, 6);
    epiP(dA, 7);
    TSC(23);
    {
      uint32_t v[16], w[16];
      float f[32] = {};
      auto addv = [&](uint32_t (&v)[16], const int i) {
        f[8 * i] += blo(v[4 * i]); f[8 * i + 1] += __uint_as_float(v[4 * i] & 0xfffe0000u); f[8 * i + 2] += blo(v[4 * i + 1]); f[8 * i + 3] += bhi(v[4 * i + 1]);
        f[8 * i + 4] += blo(v[4 * i + 2]); f[8 * i + 5] += bhi(v[4 * i + 2]); f[8 * i + 6] += blo(v[4 * i + 3]); f[8 * i + 7] += bhi(v[4 * i + 3]);
        pin8(f, 8 * i);
      };
      ldp(v, 5);
      stW(dB, 1, 1, -1);
      stW(dB, 2, 1, -1);
#pragma unroll
      for (int i = 0; i < 8; i++) {
        uint32_t t0, t1, t2, t3;
        lds128(t0, t1, t2, t3, acc + i * 2048);
        f[4 * i] = __uint_as_float(t0); f[4 * i + 1] = __uint_as_float(t1); f[4 * i + 2] = __uint_as_float(t2); f[4 * i + 3] = __uint_as_float(t3);
      }
      stW(dB, 3, 1, -1);
      ldp(w, 6);
      chk(v, 5);
      addv(v, 0); addv(v, 1);
      stW(dB, 4, 1, -1);
      addv(v, 2); addv(v, 3);
      stW(dB, 5, 1, -1);
      stO(dB, 0, -1);
      TSC(24);
      chk(w, 6);
      addv(w, 0); addv(w, 1); addv(w, 2); addv(w, 3);
      TSC(25);
      wg_wait<0>();
      TSC(26); GT(2);
      pin(dB);
      const uint32_t ps = sb + HB + wg * HHALF + STG + (warp & 3) * 2048;
      const int row = lane & 15;
#pragma unroll
      for (int t = 0; t < 8; t += 2)
        stsm4(ps + row * 128 + (((t + (lane >> 4)) ^ (row & 7)) << 4),
              pack2(f[4 * t] + dB[4 * t], f[4 * t + 1] + dB[4 * t + 1]), pack2(f[4 * t + 2] + dB[4 * t + 2], f[4 * t + 3] + dB[4 * t + 3]),
              pack2(f[4 * t + 4] + dB[4 * t + 4], f[4 * t + 5] + dB[4 * t + 5]), pack2(f[4 * t + 6] + dB[4 * t + 6], f[4 * t + 7] + dB[4 * t + 7]));
      __syncwarp();
#pragma unroll
      for (int i = 0; i < 4; i++) {
        const int rr = i * 4 + (lane >> 3), ch = lane & 7;
        uint4 o;
        lds128(o.x, o.y, o.z, o.w, ps + rr * 128 + ((ch ^ (rr & 7)) << 4));
        *reinterpret_cast<uint4*>(p.out + (size_t)(r * 128 + warp * 16 + rr) * D_ + 64 * j + ch * 8) = o;
      }
    }
    TSC(27); GT(3);
  }
}

typedef CUresult (*EncodeFn)(CUtensorMap*, CUtensorMapDataType, cuuint32_t, void*, const cuuint64_t*, const cuuint64_t*, const cuuint32_t*,
                             const cuuint32_t*, CUtensorMapInterleave, CUtensorMapSwizzle, CUtensorMapL2promotion, CUtensorMapFloatOOBfill);

CUtensorMap make_map(EncodeFn enc, const void* ptr, int rows, int cols, int brow, int bcol, CUtensorMapSwizzle sw) {
  CUtensorMap m;
  cuuint64_t gd[2] = {(cuuint64_t)cols, (cuuint64_t)rows};
  cuuint64_t gs[1] = {(cuuint64_t)cols * 2};
  cuuint32_t bd[2] = {(cuuint32_t)bcol, (cuuint32_t)brow};
  cuuint32_t es[2] = {1, 1};
  enc(&m, CU_TENSOR_MAP_DATA_TYPE_BFLOAT16, 2, const_cast<void*>(ptr), gd, gs, bd, es, CU_TENSOR_MAP_INTERLEAVE_NONE, sw,
      CU_TENSOR_MAP_L2_PROMOTION_L2_128B, CU_TENSOR_MAP_FLOAT_OOB_FILL_NONE);
  return m;
}

}

extern "C" void kernel_launch(void* const* d_in, const int* in_sizes, int n_in, void* d_out, int out_size) {
  (void)in_sizes; (void)n_in; (void)out_size;
  static EncodeFn enc = nullptr;
  static void* m_ptr = nullptr;
  if (!enc) {
    cudaGetSymbolAddress(&m_ptr, g_M);
    cudaDriverEntryPointQueryResult qr;
    cudaGetDriverEntryPoint("cuTensorMapEncodeTiled", (void**)&enc, cudaEnableDefault, &qr);
    cudaFuncSetAttribute(fused_block_kernel, cudaFuncAttributeMaxDynamicSharedMemorySize, SMEM_BYTES);
  }
  Params p;
  p.x = (const __nv_bfloat16*)d_in[0];
  p.wqkv = (const __nv_bfloat16*)d_in[1];
  p.wo = (const __nv_bfloat16*)d_in[2];
  p.w1 = (const __nv_bfloat16*)d_in[4];
  p.w3 = (const __nv_bfloat16*)d_in[5];
  p.w2 = (const __nv_bfloat16*)d_in[6];
  p.out = (__nv_bfloat16*)d_out;
  const CUtensorMap m_qkv = make_map(enc, p.wqkv, D_, 3 * D_, 96, 64, CU_TENSOR_MAP_SWIZZLE_128B);
  const CUtensorMap m_w1 = make_map(enc, p.w1, D_, F_, 96, 32, CU_TENSOR_MAP_SWIZZLE_64B);
  const CUtensorMap m_w3 = make_map(enc, p.w3, D_, F_, 96, 32, CU_TENSOR_MAP_SWIZZLE_64B);
  const CUtensorMap m_w2 = make_map(enc, p.w2, F_, D_, 96, 64, CU_TENSOR_MAP_SWIZZLE_128B);
  const CUtensorMap m_M = make_map(enc, m_ptr, 8 * 80, D_, 80, 64, CU_TENSOR_MAP_SWIZZLE_128B);
  const CUtensorMap m_x = make_map(enc, p.x, 2048, D_, 128, 64, CU_TENSOR_MAP_SWIZZLE_128B);
  fused_block_kernel<<<128, NTHREADS, SMEM_BYTES>>>(m_qkv, m_w1, m_w3, m_w2, m_M, m_x, p);
}
```

```cpp
#include <cuda_runtime.h>
#include <cuda.h>
#include <cuda_bf16.h>
#include <stdint.h>

namespace {

constexpr int D_ = 576, F_ = 4608;
constexpr int NTHREADS = 384;

constexpr uint32_t SLOT = 12288;
constexpr uint32_t HB = 6 * SLOT;
constexpr uint32_t HHALF = 73728;
constexpr uint32_t PK_T = HB + 45056;
constexpr uint32_t V_T = HB + HHALF + 18432;
constexpr uint32_t L24_T = HB + 16384;
constexpr uint32_t WO_SLOT = HB + 67584;
constexpr uint32_t OT0 = HB, OT1 = HB + 137216;
constexpr uint32_t ACC = 24576;
constexpr uint32_t STG = 49152;
constexpr uint32_t Q8 = HB + 2 * HHALF;
constexpr uint32_t WOB = Q8 + 2048;
constexpr uint32_t KVS = WOB + 5184;
constexpr uint32_t ZM = WOB;
constexpr uint32_t TAGW = KVS + 1440;
constexpr uint32_t BARS = TAGW + 32;
constexpr uint32_t SMEM_BYTES = BARS + 512;

constexpr uint32_t B_X = BARS;
constexpr uint32_t B_FULL = BARS + 8 * 9;
constexpr uint32_t B_EMPTY = BARS + 8 * 16;
constexpr uint32_t B_XDONE = BARS + 8 * 23;
constexpr uint32_t B_KVT = BARS + 8 * 24;
constexpr uint32_t B_KVD = BARS + 8 * 25;
constexpr uint32_t B_HFREE = BARS + 8 * 26;
constexpr uint32_t B_LFULL = BARS + 8 * 27;
constexpr uint32_t B_MRDY = BARS + 8 * 28;

constexpr uint32_t SPIN_LIMIT = 1u << 22;

__device__ uint4 g_part[16 * 9 * 8 * 1024];
__device__ float4 g_kvp[8 * 16 * 1280];
__device__ __align__(128) __nv_bfloat16 g_M[8 * 80 * 576];
__device__ __align__(16) float g_z[8 * 72];
__device__ uint32_t g_cnt1[8 * 32], g_cnt2[8 * 32];
__device__ uint32_t g_epoch[128];

#define TS(slot, i)
#define TSC(i)
#define GT(i)

__device__ __forceinline__ void wg_fence() { asm volatile("wgmma.fence.sync.aligned;\n" ::: "memory"); }
__device__ __forceinline__ void wg_commit() { asm volatile("wgmma.commit_group.sync.aligned;\n" ::: "memory"); }
template <int N> __device__ __forceinline__ void wg_wait() { asm volatile("wgmma.wait_group.sync.aligned %0;\n" ::"n"(N) : "memory"); }
__host__ __device__ constexpr uint64_t mkdesc(uint32_t addr, uint32_t lbo, uint32_t sbo, uint32_t sw) {
  return (uint64_t)((addr & 0x3FFFF) >> 4) | ((uint64_t)(lbo >> 4) << 16) | ((uint64_t)(sbo >> 4) << 32) | ((uint64_t)sw << 62);
}
__device__ __forceinline__ void mbar_init(uint32_t a, uint32_t c) { asm volatile("mbarrier.init.shared::cta.b64 [%0], %1;\n" ::"r"(a), "r"(c) : "memory"); }
__device__ __forceinline__ void mbar_expect(uint32_t a, uint32_t b) { asm volatile("mbarrier.arrive.expect_tx.shared::cta.b64 _, [%0], %1;\n" ::"r"(a), "r"(b) : "memory"); }
__device__ __forceinline__ void mbar_arrive(uint32_t a) { asm volatile("mbarrier.arrive.shared::cta.b64 _, [%0];\n" ::"r"(a) : "memory"); }
__device__ __forceinline__ void mbar_wait(uint32_t a, uint32_t ph) {
  asm volatile(
      "{\n.reg .pred p;\n.reg .u32 n;\n"
      "mov.u32 n, 0;\n"
      "LOOP:\n"
      "mbarrier.try_wait.parity.shared::cta.b64 p, [%0], %1;\n"
      "@p bra DONE;\n"
      "add.u32 n, n, 1;\n"
      "setp.gt.u32 p, n, %2;\n"
      "@p trap;\n"
      "bra LOOP;\n"
      "DONE:\n}\n" ::"r"(a), "r"(ph), "n"(SPIN_LIMIT) : "memory");
}
__device__ __forceinline__ void cp_async16(uint32_t dst, const void* src) {
  asm volatile("cp.async.cg.shared.global [%0], [%1], 16;\n" ::"r"(dst), "l"(src) : "memory");
}
__device__ __forceinline__ void tma2d(uint32_t dst, const CUtensorMap* m, int c0, int c1, uint32_t bar) {
  asm volatile("cp.async.bulk.tensor.2d.shared::cluster.global.mbarrier::complete_tx::bytes [%0], [%1, {%3, %4}], [%2];\n" ::"r"(dst), "l"(m), "r"(bar), "r"(c0), "r"(c1) : "memory");
}
__device__ __forceinline__ void tma2d_prefetch(const CUtensorMap* m, int c0, int c1) {
  asm volatile("cp.async.bulk.prefetch.tensor.2d.L2.global [%0, {%1, %2}];\n" ::"l"(m), "r"(c0), "r"(c1) : "memory");
}
__device__ __forceinline__ void fence_async_smem() { asm volatile("fence.proxy.async.shared::cta;\n" ::: "memory"); }
__device__ __forceinline__ void bar_sync(int id, int n) { asm volatile("bar.sync %0, %1;\n" ::"r"(id), "r"(n) : "memory"); }
__device__ __forceinline__ void ldsm4(uint32_t& r0, uint32_t& r1, uint32_t& r2, uint32_t& r3, uint32_t a) {
  asm volatile("ldmatrix.sync.aligned.m8n8.x4.shared.b16 {%0,%1,%2,%3}, [%4];\n" : "=r"(r0), "=r"(r1), "=r"(r2), "=r"(r3) : "r"(a) : "memory");
}
__device__ __forceinline__ void stsm4(uint32_t a, uint32_t r0, uint32_t r1, uint32_t r2, uint32_t r3) {
  asm volatile("stmatrix.sync.aligned.m8n8.x4.shared.b16 [%0], {%1,%2,%3,%4};\n" ::"r"(a), "r"(r0), "r"(r1), "r"(r2), "r"(r3) : "memory");
}
__device__ __forceinline__ void sts128(uint32_t a, uint32_t r0, uint32_t r1, uint32_t r2, uint32_t r3) {
  asm volatile("st.shared.v4.b32 [%0], {%1,%2,%3,%4};\n" ::"r"(a), "r"(r0), "r"(r1), "r"(r2), "r"(r3) : "memory");
}
__device__ __forceinline__ void lds128(uint32_t& r0, uint32_t& r1, uint32_t& r2, uint32_t& r3, uint32_t a) {
  asm volatile("ld.shared.v4.b32 {%0,%1,%2,%3}, [%4];\n" : "=r"(r0), "=r"(r1), "=r"(r2), "=r"(r3) : "r"(a) : "memory");
}
template <int OFF>
__device__ __forceinline__ void lds128_inplace(uint32_t (&r)[4], uint32_t a) {
  asm volatile("{\n.reg .pred p;\nsetp.ne.u32 p, %4, 0;\n@p ld.shared.v4.b32 {%0,%1,%2,%3}, [%4 + %5];\n}\n"
               : "+r"(r[0]), "+r"(r[1]), "+r"(r[2]), "+r"(r[3]) : "r"(a), "n"(OFF) : "memory");
}
__device__ __forceinline__ void sts64(uint32_t a, uint32_t r0, uint32_t r1) { asm volatile("st.shared.v2.b32 [%0], {%1,%2};\n" ::"r"(a), "r"(r0), "r"(r1) : "memory"); }
__device__ __forceinline__ void lds64(uint32_t& r0, uint32_t& r1, uint32_t a) { asm volatile("ld.shared.v2.b32 {%0,%1}, [%2];\n" : "=r"(r0), "=r"(r1) : "r"(a) : "memory"); }
__device__ __forceinline__ uint32_t lds32(uint32_t a) { uint32_t v; asm volatile("ld.shared.b32 %0, [%1];\n" : "=r"(v) : "r"(a) : "memory"); return v; }
__device__ __forceinline__ void sts32(uint32_t a, uint32_t r0) { asm volatile("st.shared.b32 [%0], %1;\n" ::"r"(a), "r"(r0) : "memory"); }
__device__ __forceinline__ void mma16816(float (&c)[4], uint32_t a0, uint32_t a1, uint32_t a2, uint32_t a3, uint32_t b0, uint32_t b1) {
  asm volatile("mma.sync.aligned.m16n8k16.row.col.f32.bf16.bf16.f32 {%0,%1,%2,%3}, {%4,%5,%6,%7}, {%8,%9}, {%0,%1,%2,%3};\n"
               : "+f"(c[0]), "+f"(c[1]), "+f"(c[2]), "+f"(c[3]) : "r"(a0), "r"(a1), "r"(a2), "r"(a3), "r"(b0), "r"(b1));
}
__device__ __forceinline__ void mma1688(float (&c)[4], uint32_t a0, uint32_t a1, uint32_t b0) {
  asm volatile("mma.sync.aligned.m16n8k8.row.col.f32.bf16.bf16.f32 {%0,%1,%2,%3}, {%4,%5}, {%6}, {%0,%1,%2,%3};\n"
               : "+f"(c[0]), "+f"(c[1]), "+f"(c[2]), "+f"(c[3]) : "r"(a0), "r"(a1), "r"(b0));
}
__device__ __forceinline__ uint32_t pack2(float lo, float hi) {
  uint32_t r;
  asm("cvt.rn.bf16x2.f32 %0, %1, %2;\n" : "=r"(r) : "f"(hi), "f"(lo));
  return r;
}
__device__ __forceinline__ float blo(uint32_t w) { return __uint_as_float(w << 16); }
__device__ __forceinline__ float bhi(uint32_t w) { return __uint_as_float(w & 0xffff0000u); }
__device__ __forceinline__ float rbf(float x) { return __bfloat162float(__float2bfloat16_rn(x)); }
__device__ __forceinline__ float ex2(float x) { float r; asm("ex2.approx.ftz.f32 %0, %1;\n" : "=f"(r) : "f"(x)); return r; }
__device__ __forceinline__ float rcp(float x) { float r; asm("rcp.approx.ftz.f32 %0, %1;\n" : "=f"(r) : "f"(x)); return r; }
__device__ __forceinline__ float sqrta(float x) { float r; asm("sqrt.approx.ftz.f32 %0, %1;\n" : "=f"(r) : "f"(x)); return r; }
__device__ __forceinline__ uint32_t bsub2(uint32_t a, uint32_t b) { uint32_t r; asm("sub.rn.bf16x2 %0, %1, %2;\n" : "=r"(r) : "r"(a), "r"(b)); return r; }
__device__ __forceinline__ uint32_t ld_acq(const uint32_t* p) { uint32_t v; asm volatile("ld.acquire.gpu.global.u32 %0, [%1];\n" : "=r"(v) : "l"(p) : "memory"); return v; }
__device__ __forceinline__ void st_b128(void* p, uint32_t a, uint32_t b, uint32_t c, uint32_t d) {
  asm volatile("st.relaxed.gpu.global.v4.b32 [%0], {%1, %2, %3, %4};\n" ::"l"(p), "r"(a), "r"(b), "r"(c), "r"(d) : "memory");
}
__device__ __forceinline__ void ld_b128(uint32_t& a, uint32_t& b, uint32_t& c, uint32_t& d, const void* p) {
  asm volatile("{\n.reg .b128 v;\nld.relaxed.gpu.global.b128 v, [%4];\nmov.b128 {%0, %1, %2, %3}, v;\n}\n" : "=r"(a), "=r"(b), "=r"(c), "=r"(d) : "l"(p) : "memory");
}
__device__ __forceinline__ bool elect_one() {
  uint32_t ok;
  asm volatile("{\n.reg .pred p;\nelect.sync _|p, 0xffffffff;\nselp.u32 %0, 1, 0, p;\n}\n" : "=r"(ok));
  return ok;
}
__device__ __forceinline__ uint32_t bmul2(uint32_t a, uint32_t b) { uint32_t r; asm("mul.rn.bf16x2 %0, %1, %2;\n" : "=r"(r) : "r"(a), "r"(b)); return r; }
__device__ __forceinline__ void red_rel(uint32_t* p) { asm volatile("red.release.gpu.global.add.u32 [%0], 1;\n" ::"l"(p) : "memory"); }
__device__ __forceinline__ void wait_ge(const uint32_t* p, uint32_t target) {
  uint32_t n = 0;
  while ((int32_t)(ld_acq(p) - target) < 0) {
    __nanosleep(64);
    if (++n > SPIN_LIMIT) __trap();
  }
}
__device__ __forceinline__ float phi(float a, float r, float rl) { return fmaf(fmaxf(a, 0.f), r, __saturatef(ex2(a * rl) + 1e-6f)); }

#define ACC8(d, o) "+f"(d[o + 0]), "+f"(d[o + 1]), "+f"(d[o + 2]), "+f"(d[o + 3]), "+f"(d[o + 4]), "+f"(d[o + 5]), "+f"(d[o + 6]), "+f"(d[o + 7])
#define REGS32 "{%0,%1,%2,%3,%4,%5,%6,%7,%8,%9,%10,%11,%12,%13,%14,%15,%16,%17,%18,%19,%20,%21,%22,%23,%24,%25,%26,%27,%28,%29,%30,%31}"
__device__ __forceinline__ void wgmma_rs64(float (&d)[32], const uint32_t (&a)[4], uint64_t db, int acc) {
  asm volatile("{\n.reg .pred p;\nsetp.ne.b32 p, %37, 0;\n"
               "wgmma.mma_async.sync.aligned.m64n64k16.f32.bf16.bf16 " REGS32 ", {%32,%33,%34,%35}, %36, p, 1, 1, 1;\n}\n"
               : ACC8(d, 0), ACC8(d, 8), ACC8(d, 16), ACC8(d, 24)
               : "r"(a[0]), "r"(a[1]), "r"(a[2]), "r"(a[3]), "l"(db), "r"(acc));
}
template <uint32_t OFF, uint32_t HI>
__device__ __forceinline__ void wgmma_ss64(float (&d)[32], uint32_t da_lo, uint64_t db) {
  asm volatile("{\n.reg .b32 lo;\n.reg .b64 da;\nadd.u32 lo, %32, %34;\nmov.b64 da, {lo, %35};\n"
               "wgmma.mma_async.sync.aligned.m64n64k16.f32.bf16.bf16 " REGS32 ", da, %33, 1, 1, 1, 0, 1;\n}\n"
               : ACC8(d, 0), ACC8(d, 8), ACC8(d, 16), ACC8(d, 24)
               : "r"(da_lo), "l"(db), "n"(OFF), "n"(HI));
}
__device__ __forceinline__ void wgmma_rs24(float (&d)[12], const uint32_t (&a)[4], uint64_t db, int acc) {
  asm volatile("{\n.reg .pred p;\nsetp.ne.b32 p, %17, 0;\n"
               "wgmma.mma_async.sync.aligned.m64n24k16.f32.bf16.bf16 {%0,%1,%2,%3,%4,%5,%6,%7,%8,%9,%10,%11}, {%12,%13,%14,%15}, %16, p, 1, 1, 1;\n}\n"
               : ACC8(d, 0), "+f"(d[8]), "+f"(d[9]), "+f"(d[10]), "+f"(d[11])
               : "r"(a[0]), "r"(a[1]), "r"(a[2]), "r"(a[3]), "l"(db), "r"(acc));
}
__device__ __forceinline__ void wgmma_ss40tt(float (&d)[20], uint64_t da, uint64_t db, int acc) {
  asm volatile("{\n.reg .pred p;\nsetp.ne.b32 p, %22, 0;\n"
               "wgmma.mma_async.sync.aligned.m64n40k16.f32.bf16.bf16 {%0,%1,%2,%3,%4,%5,%6,%7,%8,%9,%10,%11,%12,%13,%14,%15,%16,%17,%18,%19}, %20, %21, p, 1, 1, 1, 1;\n}\n"
               : ACC8(d, 0), ACC8(d, 8), "+f"(d[16]), "+f"(d[17]), "+f"(d[18]), "+f"(d[19])
               : "l"(da), "l"(db), "r"(acc));
}
template <uint32_t OFF, uint32_t HI, int ACCUM>
__device__ __forceinline__ void wgmma_ss16(float (&d)[8], uint32_t da_lo, uint64_t db) {
  asm volatile("{\n.reg .b32 lo;\n.reg .b64 da;\n.reg .pred p;\nsetp.ne.b32 p, %12, 0;\nadd.u32 lo, %8, %10;\nmov.b64 da, {lo, %11};\n"
               "wgmma.mma_async.sync.aligned.m64n16k16.f32.bf16.bf16 {%0,%1,%2,%3,%4,%5,%6,%7}, da, %9, p, 1, 1, 0, 1;\n}\n"
               : ACC8(d, 0)
               : "r"(da_lo), "l"(db), "n"(OFF), "n"(HI), "n"(ACCUM));
}
template <int N> __device__ __forceinline__ void pin(float (&d)[N]) {
#pragma unroll
  for (int i = 0; i < N; i++) asm volatile("" : "+f"(d[i])::"memory");
}

__device__ __forceinline__ void pin8(float (&d)[32], const int o) { asm volatile("" : ACC8(d, o)::"memory"); }

struct Params {
  const __nv_bfloat16* x;
  const __nv_bfloat16* wqkv;
  const __nv_bfloat16* wo;
  const __nv_bfloat16* w1;
  const __nv_bfloat16* w3;
  const __nv_bfloat16* w2;
  __nv_bfloat16* out;
};

__global__ void __launch_bounds__(NTHREADS, 1)
fused_block_kernel(const __grid_constant__ CUtensorMap m_qkv, const __grid_constant__ CUtensorMap m_w1,
                   const __grid_constant__ CUtensorMap m_w3, const __grid_constant__ CUtensorMap m_w2,
                   const __grid_constant__ CUtensorMap m_M, const __grid_constant__ CUtensorMap m_x, const Params p) {
  extern __shared__ __align__(1024) uint8_t smem_raw[];
  constexpr uint32_t sb = 1024;
  if ((uint32_t)__cvta_generic_to_shared(smem_raw) != sb) __trap();
  const int tid = threadIdx.x, warp = __shfl_sync(0xffffffffu, tid >> 5, 0), lane = tid & 31;
  const int r = blockIdx.x >> 3, j = blockIdx.x & 7;

  GT(0); TSC(0);
  const int cmain = 72 * j + 8 * (j & 1);
  if (__builtin_expect(warp >= 8, 1)) {
    asm volatile("setmaxnreg.dec.sync.aligned.u32 24;\n");
    if (__builtin_expect(warp == 8, 1)) {
      const bool leader = elect_one();
      if (leader) {
#pragma unroll
        for (int b = 0; b < 9; b++) mbar_init(sb + B_X + 8 * b, 1);
        asm volatile("fence.mbarrier_init.release.cluster;\n" ::: "memory");
        mbar_expect(sb + B_X, 16384);
        tma2d(sb + HB, &m_x, 0, 128 * r, sb + B_X);
#pragma unroll
        for (int i = 9; i < 29; i++) mbar_init(sb + BARS + 8 * i, i < 16 ? 1 : i < 27 ? 8 : 96);
        asm volatile("fence.mbarrier_init.release.cluster;\n" ::: "memory");
      }
      __syncwarp();
      asm volatile("bar.arrive 0, 384;\n" ::: "memory");
      if (elect_one()) {
#pragma unroll
        for (int b = 1; b < 9; b++) {
          mbar_expect(sb + B_X + 8 * b, 16384);
          tma2d(sb + HB + b * 16384, &m_x, 64 * b, 128 * r, sb + B_X + 8 * b);
        }
#pragma unroll
        for (int s = 0; s < 6; s++) {
          mbar_expect(sb + B_FULL + 8 * s, SLOT);
          tma2d(sb + s * SLOT, &m_qkv, D_ + cmain, 96 * s, sb + B_FULL + 8 * s);
        }
        const CUtensorMap* mpf = (r & 1) ? &m_w3 : &m_w1;
        if (r < 6) tma2d_prefetch(&m_qkv, 2 * D_ + cmain, 96 * r);
        if (r < 12) { tma2d_prefetch(mpf, 576 * j, 96 * (r >> 1)); tma2d_prefetch(mpf, 576 * j + 32, 96 * (r >> 1)); }
#pragma unroll
        for (int s = 0; s < 6; s++) {
          mbar_wait(sb + B_EMPTY + 8 * s, 0);
          mbar_expect(sb + B_FULL + 8 * s, SLOT);
          tma2d(sb + s * SLOT, &m_qkv, 2 * D_ + cmain, 96 * s, sb + B_FULL + 8 * s);
        }
#pragma unroll 1
        for (int n = 0; n < 18; n++) {
          const int col = 576 * j + 32 * n;
          if (n < 16) { if (r < 12) tma2d_prefetch(mpf, col + 64, 96 * (r >> 1)); }
          else if (r < 6) {
            if (n == 16) tma2d_prefetch(&m_qkv, cmain, 96 * r);
            else tma2d_prefetch(&m_w2, 512, 576 * j + 96 * r);
          }
#pragma unroll
          for (int s = 0; s < 6; s++) {
            mbar_wait(sb + B_EMPTY + 8 * s, (n & 1) ^ 1);
            mbar_expect(sb + B_FULL + 8 * s, SLOT);
            tma2d(sb + s * SLOT, &m_w1, col, 96 * s, sb + B_FULL + 8 * s);
            tma2d(sb + s * SLOT + SLOT / 2, &m_w3, col, 96 * s, sb + B_FULL + 8 * s);
          }
        }
        if (r < 6) tma2d_prefetch(&m_w2, 64 * ((j + 1) & 7), 576 * j + 96 * r);
#pragma unroll
        for (int s = 0; s < 6; s++) {
          mbar_wait(sb + B_EMPTY + 8 * s, 1);
          mbar_expect(sb + B_FULL + 8 * s, SLOT);
          tma2d(sb + s * SLOT, &m_qkv, cmain, 96 * s, sb + B_FULL + 8 * s);
        }
#pragma unroll 1
        for (int n = 0; n < 9; n++) {
          const int col = n == 0 ? 512 : 64 * ((j + n) & 7);
          if (n < 7 && r < 6) tma2d_prefetch(&m_w2, 64 * ((j + n + 2) & 7), 576 * j + 96 * r);
#pragma unroll
          for (int s = 0; s < 6; s++) {
            mbar_wait(sb + B_EMPTY + 8 * s, n & 1);
            mbar_expect(sb + B_FULL + 8 * s, SLOT);
            tma2d(sb + s * SLOT, &m_w2, col, 576 * j + 96 * s, sb + B_FULL + 8 * s);
          }
          if (n == 0) {
            mbar_wait(sb + B_HFREE, 0);
            mbar_wait(sb + B_MRDY, 0);
            asm volatile("fence.proxy.async;\n" ::: "memory");
          }
          mbar_wait(sb + B_EMPTY + 48, (n & 1) ^ 1);
          mbar_expect(sb + B_FULL + 48, 80 * 128);
          tma2d(sb + WO_SLOT, &m_M, col, 80 * j, sb + B_FULL + 48);
        }
      }
    } else {
      const int ht = tid - 288;
      if (ht == 0) asm volatile("prefetch.tensormap [%0];\n" ::"l"(&m_qkv) : "memory");
      asm volatile("bar.sync 0, 384;\n" ::: "memory");
      const uint32_t ep = g_epoch[blockIdx.x] + 1;
      mbar_wait(sb + B_X + 8 * 8, 0);
      if (ht < 90) {
        const int e = ht / 18, c = ht - e * 18;
        const __nv_bfloat16* w = p.wo + (size_t)(72 * j + 18 * (r >> 2) + e) * D_ + 144 * (r & 3) + c * 8;
#pragma unroll
        for (int i = 0; i < 4; i++)
          if (i < 3 || ht < 54) cp_async16(sb + WOB + ht * 16 + i * 90 * 16, w + i * 5 * D_);
      }
      const __nv_bfloat16* wl = p.wqkv + (size_t)ht * (3 * D_) + 72 * j + ((j & 1) ? 0 : 64);
      mbar_wait(sb + B_XDONE, 0);
#pragma unroll
      for (int g = 0; g < 3; g++)
#pragma unroll
        for (int m = 0; m < 6; m++) cp_async16(sb + L24_T + g * 9216 + m * 96 * 16 + ht * 16, wl + (size_t)m * 96 * 3 * D_ + (g == 2 ? 0 : (g + 1) * D_));
      if (ht < 64) {
#pragma unroll
        for (int i = 0; i < 4; i++) sts128(sb + V_T - 2048 + (i >> 1) * 20480 + (i & 1) * 1024 + ht * 16, 0x3F803F80u, 0x3F803F80u, 0x3F803F80u, 0x3F803F80u);
      }
      asm volatile("cp.async.wait_all;\n" ::: "memory");
      fence_async_smem();
      mbar_arrive(sb + B_LFULL);
      if (warp == 9) TS(3, 1);

      if (ht == 0) {
        mbar_wait(sb + B_KVD, 0);
        red_rel(&g_cnt1[j * 32]);
        wait_ge(&g_cnt1[j * 32], 16 * ep);
      }
      bar_sync(3, 96);
      if (warp == 9) TS(3, 4);
#pragma unroll 1
      for (int i = ht; i < 171; i += 96) {
        const int dp = i / 19, el = i - dp * 19, hd = r >> 2, w = hd >> 1;
        const int d = 18 * hd + 2 * dp - 32 * w;
        const int m = el == 18 ? 56 * w : 18 * hd + el + 8 - 24 * w;
        const float2* src = reinterpret_cast<const float2*>(g_kvp + j * 16 * 1280 + ((w * 4 + (m >> 4)) * 5 + (d >> 3)) * 32 + (m & 7) * 4 + ((d & 7) >> 1)) + ((m >> 3) & 1);
        float s0 = 0.f, s1 = 0.f;
#pragma unroll 1
        for (int r4 = 0; r4 < 4; r4++) {
          const float2 v0 = __ldcg(src), v1 = __ldcg(src + 2560), v2 = __ldcg(src + 2 * 2560), v3 = __ldcg(src + 3 * 2560);
          s0 += (v0.x + v1.x) + (v2.x + v3.x);
          s1 += (v0.y + v1.y) + (v2.y + v3.y);
          src += 4 * 2560;
        }
        sts64(sb + KVS + dp * 160 + el * 8, __float_as_uint(s0), __float_as_uint(s1));
        if ((r & 3) == 0 && el == 18) *reinterpret_cast<float2*>(g_z + j * 72 + hd * 18 + dp * 2) = make_float2(s0, s1);
      }
      bar_sync(3, 96);
      if (warp == 9) TS(3, 5);
#pragma unroll 1
      for (int t = ht; t < 648; t += 96) {
        const int dp = t / 72, cp = t - dp * 72;
        float c0 = 0.f, c1 = 0.f, c2 = 0.f, c3 = 0.f;
        const uint32_t ka = sb + KVS + dp * 160, wa = sb + WOB + cp * 4;
#pragma unroll
        for (int e2 = 0; e2 < 9; e2++) {
          uint32_t a0, a1, a2, a3;
          lds128(a0, a1, a2, a3, ka + e2 * 16);
          const uint32_t w0 = lds32(wa + e2 * 576), w1 = lds32(wa + e2 * 576 + 288);
          c0 = fmaf(__uint_as_float(a0), blo(w0), c0); c1 = fmaf(__uint_as_float(a0), bhi(w0), c1);
          c2 = fmaf(__uint_as_float(a1), blo(w0), c2); c3 = fmaf(__uint_as_float(a1), bhi(w0), c3);
          c0 = fmaf(__uint_as_float(a2), blo(w1), c0); c1 = fmaf(__uint_as_float(a2), bhi(w1), c1);
          c2 = fmaf(__uint_as_float(a3), blo(w1), c2); c3 = fmaf(__uint_as_float(a3), bhi(w1), c3);
        }
        const int d = 18 * (r >> 2) + 2 * dp;
        uint32_t* dst = reinterpret_cast<uint32_t*>(g_M) + (80 * j + ((j & 1) ? (d < 8 ? d + 64 : d - 8) : d)) * 288 + 72 * (r & 3) + cp;
        dst[0] = pack2(c0, c1);
        dst[288] = pack2(c2, c3);
      }
      asm volatile("fence.proxy.async;\n" ::: "memory");
      bar_sync(3, 96);
      if (warp == 9) TS(3, 6);
      if (ht == 0) { red_rel(&g_cnt2[j * 32]); wait_ge(&g_cnt2[j * 32], 16 * ep); }
      bar_sync(3, 96);
      if (ht < 80) {
        const int d = (j & 1) ? (ht < 64 ? ht + 8 : ht - 64) : ht;
        uint32_t zb = 0;
        if (ht < 72) zb = pack2(__ldcg(g_z + j * 72 + d), 0.f);
        const int hd = d / 18;
        const uint32_t w = (hd & 1) ? zb << 16 : zb;
        const uint32_t w0 = hd < 2 ? w : 0u, w1 = hd < 2 ? 0u : w;
        sts128(sb + ZM + ht * 16, w0, w0, w0, w0);
        sts128(sb + ZM + 1280 + ht * 16, w1, w1, w1, w1);
      }
      const uint32_t tag = (ep & 1) << 16;
      if (ht == 95) { sts32(sb + TAGW, tag); g_epoch[blockIdx.x] = ep; }
      fence_async_smem();
      mbar_arrive(sb + B_MRDY);
      if (warp == 9) TS(3, 7);
      if (warp < 11) {
        mbar_wait(sb + B_FULL + 48, 0);
#pragma unroll 1
        for (int i = warp - 9; i < 4; i += 2) {
          const uint4* src = g_part + (size_t)((r * 9 + 8) * 8) * 1024 + j * 128 + i * 32 + lane;
          const int off = ((r * 128 + j * 16 + (lane >> 2)) * D_ + 512 + 16 * i + 2 * (lane & 3)) >> 1;
          float s0, s1, s2, s3, s4, s5, s6, s7;
          {
            const uint32_t* xp = reinterpret_cast<const uint32_t*>(p.x) + off;
            const uint32_t x0 = __ldg(xp), x1 = __ldg(xp + 4 * D_), x2 = __ldg(xp + 4), x3 = __ldg(xp + 4 * D_ + 4);
            s0 = blo(x0); s1 = bhi(x0); s2 = blo(x1); s3 = bhi(x1); s4 = blo(x2); s5 = bhi(x2); s6 = blo(x3); s7 = bhi(x3);
          }
          uint32_t n = 0;
#pragma unroll 1
          for (int jj = 0; jj < 8;) {
            uint32_t v0, v1, v2, v3;
            ld_b128(v0, v1, v2, v3, src);
            if (__all_sync(0xffffffffu, ((v0 ^ tag) & 0x10000u) == 0)) {
              s0 += blo(v0); s1 += __uint_as_float(v0 & 0xfffe0000u); s2 += blo(v1); s3 += bhi(v1);
              s4 += blo(v2); s5 += bhi(v2); s6 += blo(v3); s7 += bhi(v3);
              jj++;
              src += 1024;
            } else {
              __nanosleep(200);
              if (++n > SPIN_LIMIT) __trap();
            }
          }
          uint32_t* op = reinterpret_cast<uint32_t*>(p.out) + off;
          op[0] = pack2(s0, s1); op[4 * D_] = pack2(s2, s3); op[4] = pack2(s4, s5); op[4 * D_ + 4] = pack2(s6, s7);
        }
        if (warp == 9) TS(3, 10);
      }
    }
  } else {
    asm volatile("setmaxnreg.inc.sync.aligned.u32 240;\n");
    asm volatile("bar.sync 0, 384;\n" ::: "memory");
    const int wg = warp >> 2;
    uint32_t a[36][4];
    float dA[32], dB[32];
    const bool l0 = lane == 0;
    constexpr uint64_t dsw128 = mkdesc(sb, 16, 1024, 1);
    constexpr uint64_t dsw64 = mkdesc(sb, SLOT / 2, 512, 2);

    auto issue = [&](float (&d)[32], const uint64_t dbase, const int kstride, const int s, const uint32_t ph) {
      mbar_wait(sb + B_FULL + 8 * s, ph);
      wg_fence();
#pragma unroll
      for (int ks = 0; ks < 6; ks++) wgmma_rs64(d, a[s * 6 + ks], dbase + ((s * SLOT + ks * kstride) >> 4), (s | ks) != 0);
    };
    auto finish = [&](const int rel) {
      wg_commit();
      wg_wait<1>();
      if (rel >= 0 && l0) mbar_arrive(sb + B_EMPTY + 8 * rel);
    };
    auto stW = [&](float (&d)[32], const int s, const uint32_t ph, const int rel) { issue(d, dsw128, 2048, s, ph); finish(rel); };
    auto stF = [&](float (&d)[32], const int s, const uint32_t ph, const int rel) { issue(d, dsw64, 1024, s, ph); finish(rel); };

    TSC(1);
    uint32_t mb0, mb1;
    float r0, r1;
    auto center = [&](const int g) {
#pragma unroll
      for (int ks = 6 * g; ks < 6 * g + 6; ks++) {
        a[ks][0] = bsub2(a[ks][0], mb0); a[ks][1] = bsub2(a[ks][1], mb1);
        a[ks][2] = bsub2(a[ks][2], mb0); a[ks][3] = bsub2(a[ks][3], mb1);
        asm volatile("" : "+r"(a[ks][0]), "+r"(a[ks][1]), "+r"(a[ks][2]), "+r"(a[ks][3])::"memory");
      }
    };
    {
      const uint32_t xa = sb + HB + (warp * 16 + (lane & 15)) * 128;
      const uint32_t sw = lane & 7, hi = lane >> 4;
      constexpr uint32_t ONES = 0x3F803F80u;
      float cs[2][4], cq[4][4];
#pragma unroll
      for (int i = 0; i < 4; i++) { cs[0][i] = cs[1][i] = cq[0][i] = cq[1][i] = cq[2][i] = cq[3][i] = 0.f; }
      auto gram = [&](const uint32_t (&e)[4]) {
        mma1688(cq[0], e[0], e[1], e[0]); mma1688(cq[1], e[0], e[1], e[1]);
        mma1688(cq[2], e[2], e[3], e[2]); mma1688(cq[3], e[2], e[3], e[3]);
      };
#pragma unroll
      for (int b = 0; b < 9; b++) {
        mbar_wait(sb + B_X + 8 * b, 0);
        if (b == 0 || b == 8) TSC(32 + b);
#pragma unroll
        for (int kk = 0; kk < 4; kk++) ldsm4(a[4 * b + kk][0], a[4 * b + kk][1], a[4 * b + kk][2], a[4 * b + kk][3], xa + b * 16384 + (((2 * kk + hi) ^ sw) << 4));
        if (b > 0) {
#pragma unroll
          for (int kk = 0; kk < 4; kk++) gram(a[4 * b - 4 + kk]);
        }
#pragma unroll
        for (int kk = 0; kk < 4; kk++) mma16816(cs[kk & 1], a[4 * b + kk][0], a[4 * b + kk][1], a[4 * b + kk][2], a[4 * b + kk][3], ONES, ONES);
      }
#pragma unroll
      for (int kk = 0; kk < 4; kk++) gram(a[32 + kk]);
      TSC(2);
      const float m0 = (cs[0][0] + cs[1][0]) * (1.f / 576.f), m1 = (cs[0][2] + cs[1][2]) * (1.f / 576.f);
      mb0 = pack2(m0, m0);
      mb1 = pack2(m1, m1);
      center(0);
      TSC(3);
      stW(dA, 0, 0, -1);
      center(1);
      stW(dA, 1, 0, 0);
      const bool godd = lane & 4;
      const int src = (lane & ~3) | (lane >> 3);
      const float q0 = __shfl_sync(0xffffffffu, godd ? cq[0][1] + cq[2][1] : cq[0][0] + cq[2][0], src) * (1.f / 576.f);
      const float q1 = __shfl_sync(0xffffffffu, godd ? cq[1][3] + cq[3][3] : cq[1][2] + cq[3][2], src) * (1.f / 576.f);
      float v0 = q0 - m0 * m0, v1 = q1 - m1 * m1;
      if (__any_sync(0xffffffffu, v0 < q0 * (1.f / 64.f) || v1 < q1 * (1.f / 64.f))) {
        float s0 = 0.f, s1 = 0.f;
#pragma unroll 1
        for (int ks = 0; ks < 36; ks++) {
          uint32_t e0, e1, e2, e3;
          ldsm4(e0, e1, e2, e3, xa + (ks >> 2) * 16384 + (((2 * (ks & 3) + hi) ^ sw) << 4));
          float t;
          t = blo(e0) - m0; s0 = fmaf(t, t, s0); t = bhi(e0) - m0; s0 = fmaf(t, t, s0);
          t = blo(e2) - m0; s0 = fmaf(t, t, s0); t = bhi(e2) - m0; s0 = fmaf(t, t, s0);
          t = blo(e1) - m1; s1 = fmaf(t, t, s1); t = bhi(e1) - m1; s1 = fmaf(t, t, s1);
          t = blo(e3) - m1; s1 = fmaf(t, t, s1); t = bhi(e3) - m1; s1 = fmaf(t, t, s1);
        }
        s0 += __shfl_xor_sync(0xffffffffu, s0, 1); s1 += __shfl_xor_sync(0xffffffffu, s1, 1);
        s0 += __shfl_xor_sync(0xffffffffu, s0, 2); s1 += __shfl_xor_sync(0xffffffffu, s1, 2);
        v0 = s0 * (1.f / 576.f); v1 = s1 * (1.f / 576.f);
      }
      __syncwarp();
      if (l0) mbar_arrive(sb + B_XDONE);
      r0 = rcp(rbf(sqrta(rbf(rbf(fmaxf(v0, 0.f)) + 1e-5f))));
      r1 = rcp(rbf(sqrta(rbf(rbf(fmaxf(v1, 0.f)) + 1e-5f))));
    }
#pragma unroll
    for (int s = 2; s < 6; s++) {
      center(s);
      stW(dA, s, 0, s - 1);
    }
    TSC(4); GT(1);
    constexpr float LOG2E = 1.4426950408889634f;
    float l0e = r0 * LOG2E, l1e = r1 * LOG2E;
    const uint32_t tile_off = ((lane >> 4) + (j & 1)) * 2048 + (warp * 16 + (lane & 15)) * 16;
    mbar_wait(sb + B_XDONE, 0);
#pragma unroll
    for (int s = 0; s < 6; s++) {
      stW(dB, s, 1, (s + 5) % 6);
      if (s < 4) {
        const int t = 2 * s;
        pin8(dA, 4 * t);
        stsm4(sb + PK_T + tile_off + t * 2048, pack2(phi(dA[4 * t], r0, l0e), phi(dA[4 * t + 1], r0, l0e)), pack2(phi(dA[4 * t + 2], r1, l1e), phi(dA[4 * t + 3], r1, l1e)),
              pack2(phi(dA[4 * t + 4], r0, l0e), phi(dA[4 * t + 5], r0, l0e)), pack2(phi(dA[4 * t + 6], r1, l1e), phi(dA[4 * t + 7], r1, l1e)));
      }
    }
    TSC(5);
    {
#pragma unroll
      for (int s = 0; s < 2; s++) {
        stF(dA, s, 0, (s + 5) % 6);
#pragma unroll
        for (int t = 4 * s; t < 4 * s + 4; t += 2) {
          pin8(dB, 4 * t);
          stsm4(sb + V_T + tile_off + t * 2048, pack2(dB[4 * t] * r0, dB[4 * t + 1] * r0), pack2(dB[4 * t + 2] * r1, dB[4 * t + 3] * r1),
                pack2(dB[4 * t + 4] * r0, dB[4 * t + 5] * r0), pack2(dB[4 * t + 6] * r1, dB[4 * t + 7] * r1));
        }
      }
      float dL[12];
      constexpr uint64_t dl = mkdesc(sb + L24_T, 128, 576 * 16, 0);
      mbar_wait(sb + B_LFULL, 0);
#pragma unroll
      for (int s = 2; s < 5; s++) {
        mbar_wait(sb + B_FULL + 8 * s, 0);
        wg_fence();
#pragma unroll
        for (int ks = 12 * (s - 2); ks < 12 * (s - 1); ks++) wgmma_rs24(dL, a[ks], dl + ks * 16, ks != 0);
#pragma unroll
        for (int ks = 0; ks < 6; ks++) wgmma_rs64(dA, a[s * 6 + ks], dsw64 + ((s * SLOT + ks * 1024) >> 4), 1);
        finish(s - 1);
      }
      stF(dA, 5, 0, 4);
      pin(dL);
      const uint32_t lo = ((j & 1) ? 0 : 8 * 2048) + warp * 256 + lane * 4;
      sts32(sb + PK_T + lo, pack2(phi(dL[0], r0, l0e), phi(dL[1], r0, l0e)));
      sts32(sb + PK_T + lo + 128, pack2(phi(dL[2], r1, l1e), phi(dL[3], r1, l1e)));
      sts32(sb + V_T + lo, pack2(dL[4] * r0, dL[5] * r0));
      sts32(sb + V_T + lo + 128, pack2(dL[6] * r1, dL[7] * r1));
      sts64(sb + Q8 + tid * 8, pack2(dL[8], dL[9]), pack2(dL[10], dL[11]));
      fence_async_smem();
      __syncwarp();
      if (l0) mbar_arrive(sb + B_KVT);
    }
    TSC(6);
    uint32_t hs = sb + HB + wg * HHALF + (tid & 127) * 16;
    uint32_t hp0, hp1;
    const float iq0 = rcp(r0 * r0), iq1 = rcp(r1 * r1);
    auto epiF = [&](float (&d)[32], const int pc) {
      asm volatile("" : "+f"(d[4 * pc]), "+f"(d[4 * pc + 1]), "+f"(d[4 * pc + 2]), "+f"(d[4 * pc + 3]), "+f"(d[4 * pc + 16]), "+f"(d[4 * pc + 17]),
                   "+f"(d[4 * pc + 18]), "+f"(d[4 * pc + 19])::"memory");
      const float g0 = d[4 * pc], g1 = d[4 * pc + 1], g2 = d[4 * pc + 2], g3 = d[4 * pc + 3];
      const uint32_t h0 = pack2(g0 * d[4 * pc + 16] * rcp(fmaf(ex2(-g0 * l0e), iq0, iq0)), g1 * d[4 * pc + 17] * rcp(fmaf(ex2(-g1 * l0e), iq0, iq0)));
      const uint32_t h1 = pack2(g2 * d[4 * pc + 18] * rcp(fmaf(ex2(-g2 * l1e), iq1, iq1)), g3 * d[4 * pc + 19] * rcp(fmaf(ex2(-g3 * l1e), iq1, iq1)));
      if (pc & 1) {
        sts128(hs, hp0, hp1, h0, h1);
        hs += 2048;
      } else {
        hp0 = h0; hp1 = h1;
        asm volatile("" : "+r"(hp0), "+r"(hp1)::"memory");
      }
    };
    {
      stF(dB, 0, 1, 5);
      epiF(dA, 0); epiF(dA, 1);
      stF(dB, 1, 1, 0);
      epiF(dA, 2); epiF(dA, 3);
      float dK[20];
      const uint64_t ka = mkdesc(sb + V_T - 2048 + wg * 3 * 2048, 128, 2048, 0), kb = mkdesc(sb + PK_T + wg * 4 * 2048, 128, 2048, 0);
      mbar_wait(sb + B_KVT, 0);
      mbar_wait(sb + B_FULL + 8 * 2, 1);
      wg_fence();
#pragma unroll
      for (int ks = 0; ks < 8; ks++) wgmma_ss40tt(dK, ka + ks * 16, kb + ks * 16, ks != 0);
#pragma unroll
      for (int ks = 0; ks < 6; ks++) wgmma_rs64(dB, a[12 + ks], dsw64 + ((2 * SLOT + ks * 1024) >> 4), 1);
      finish(1);
      stF(dB, 3, 1, 2);
      pin(dK);
      float4* dst = g_kvp + (j * 16 + r) * 1280 + warp * 160 + lane;
#pragma unroll
      for (int t = 0; t < 5; t++) __stcg(dst + t * 32, make_float4(dK[4 * t], dK[4 * t + 1], dK[4 * t + 2], dK[4 * t + 3]));
      __syncwarp();
      if (l0) mbar_arrive(sb + B_KVD);
      stF(dB, 4, 1, 3);
    }
#pragma unroll 1
    for (int it = 0; it < 8; it++) {
      stF(dB, 5, 1, 4);
      stF(dA, 0, 0, 5);
#pragma unroll
      for (int s = 1; s < 5; s++) { epiF(dB, s - 1); stF(dA, s, 0, s - 1); }
      stF(dA, 5, 0, 4);
      stF(dB, 0, 1, 5);
#pragma unroll
      for (int s = 1; s < 5; s++) { epiF(dA, s - 1); stF(dB, s, 1, s - 1); }
      TSC(7 + it);
    }
    stF(dB, 5, 1, 4);
    TSC(15);
    const uint32_t hl = sb + HB + wg * HHALF + (tid & 127) * 16;
    auto reload = [&](const int g) {
      const uint32_t ha = hl + g * 12288;
      lds128_inplace<0>(a[6 * g], ha); lds128_inplace<2048>(a[6 * g + 1], ha); lds128_inplace<4096>(a[6 * g + 2], ha);
      lds128_inplace<6144>(a[6 * g + 3], ha); lds128_inplace<8192>(a[6 * g + 4], ha); lds128_inplace<10240>(a[6 * g + 5], ha);
    };
    stW(dA, 0, 0, 5);
#pragma unroll
    for (int s = 1; s < 6; s++) {
      if (s < 5) epiF(dB, s - 1);
      stW(dA, s, 0, s - 1);
      reload(s - 1);
    }
    const uint32_t ot = sb + (wg ? OT1 : OT0);
    const uint32_t do_a = (uint32_t)mkdesc(ot, 128, 1280, 0);
    constexpr uint64_t do_b = mkdesc(sb + WO_SLOT, 16, 1024, 1);
    auto stO = [&](float (&d)[32], const uint32_t ph, const int rel) {
      mbar_wait(sb + B_FULL + 48, ph);
      wg_fence();
      wgmma_ss64<0, 80>(d, do_a, do_b);
      wgmma_ss64<16, 80>(d, do_a, do_b + 128);
      wgmma_ss64<32, 80>(d, do_a, do_b + 256);
      wgmma_ss64<48, 80>(d, do_a, do_b + 384);
      wgmma_ss64<64, 80>(d, do_a, do_b + 512);
      finish(rel);
    };
    uint32_t tag;
    auto epiP = [&](float (&d)[32], const int step) {
      pin(d);
      const int c = step == 0 ? 8 : ((j + step) & 7);
      uint4* dst = g_part + (size_t)((r * 9 + c) * 8 + j) * 1024 + warp * 128 + lane;
#pragma unroll
      for (int i = 0; i < 4; i++)
        st_b128(dst + i * 32, (pack2(d[8 * i], d[8 * i + 1]) & 0xfffeffffu) | tag, pack2(d[8 * i + 2], d[8 * i + 3]), pack2(d[8 * i + 4], d[8 * i + 5]), pack2(d[8 * i + 6], d[8 * i + 7]));
    };
    TSC(16);
    {
      stW(dB, 0, 1, 5);
      reload(5);
      asm volatile("" : "+f"(l0e), "+f"(l1e));
      r0 = l0e * (1.f / LOG2E); r1 = l1e * (1.f / LOG2E);
      uint32_t pq[18];
      fence_async_smem();
      __syncwarp();
      if (l0) mbar_arrive(sb + B_HFREE);
      const uint32_t oa = ot + ((warp & 3) * 2 + ((lane >> 3) & 1)) * 1280 + (lane >> 4) * 128 + (lane & 7) * 16;
      auto phiq = [&](const int t0, const int t1) {
#pragma unroll
        for (int t = t0; t < t1; t++) {
          asm volatile("" : "+f"(dA[4 * t]), "+f"(dA[4 * t + 1]), "+f"(dA[4 * t + 2]), "+f"(dA[4 * t + 3])::"memory");
          pq[2 * t] = pack2(phi(dA[4 * t], r0, l0e), phi(dA[4 * t + 1], r0, l0e));
          pq[2 * t + 1] = pack2(phi(dA[4 * t + 2], r1, l1e), phi(dA[4 * t + 3], r1, l1e));
          asm volatile("" : "+r"(pq[2 * t]), "+r"(pq[2 * t + 1])::"memory");
        }
      };
      phiq(0, 3);
      stW(dB, 1, 1, 0);
      phiq(3, 6);
      bar_sync(1 + wg, 128);
      stW(dB, 2, 1, 1);
      phiq(6, 8);
      {
        uint32_t q0, q1;
        lds64(q0, q1, sb + Q8 + tid * 8);
        pq[16] = pack2(phi(blo(q0), r0, l0e), phi(bhi(q0), r0, l0e));
        pq[17] = pack2(phi(blo(q1), r1, l1e), phi(bhi(q1), r1, l1e));
      }
#pragma unroll
      for (int t = 0; t < 8; t += 2) stsm4(oa + t * 128, pq[2 * t], pq[2 * t + 1], pq[2 * t + 2], pq[2 * t + 3]);
      stsm4(oa + 1024, pq[16], pq[17], 0u, 0u);
      fence_async_smem();
      TSC(17);
      mbar_wait(sb + B_MRDY, 0);
      TSC(18);
      tag = lds32(sb + TAGW);
      float den[8];
      constexpr uint64_t dz = mkdesc(sb + ZM, 128, 1280, 0);
      bar_sync(1 + wg, 128);
      issue(dB, dsw128, 2048, 3, 1);
      wgmma_ss16<0, 80, 0>(den, do_a, dz);
      wgmma_ss16<16, 80, 1>(den, do_a, dz + 16);
      wgmma_ss16<32, 80, 1>(den, do_a, dz + 32);
      wgmma_ss16<48, 80, 1>(den, do_a, dz + 48);
      wgmma_ss16<64, 80, 1>(den, do_a, dz + 64);
      finish(2);
      stW(dB, 4, 1, 3);
      pin(den);
      uint32_t iv[8];
#pragma unroll
      for (int i = 0; i < 8; i++) { const float t = rcp(den[i] + 1e-6f); iv[i] = pack2(t, t); }
      const int u = 2 * (lane & 3) + 8 * (j & 1);
#pragma unroll
      for (int t = 0; t < 10; t += 2) {
        uint32_t o[4];
#pragma unroll
        for (int z = 0; z < 2; z++) {
          const int tt = t + z;
          if (tt < 9) {
            const int lo = tt == 0 ? 0 : tt >= 7 ? 3 : (tt - 1) >> 1, hi = tt == 8 ? 0 : (tt == 0 || tt == 7) ? lo : lo + 1;
            const bool up = tt == 8 ? (j & 1) : 8 * tt + u >= 18 * hi;
            const int il = (lo >> 1) * 4 + (lo & 1), ih = (hi >> 1) * 4 + (hi & 1);
            o[2 * z] = bmul2(pq[2 * tt], up ? iv[ih] : iv[il]);
            o[2 * z + 1] = bmul2(pq[2 * tt + 1], up ? iv[ih + 2] : iv[il + 2]);
          } else {
            o[2 * z] = 0; o[2 * z + 1] = 0;
          }
        }
        stsm4(oa + t * 128, o[0], o[1], o[2], o[3]);
      }
      fence_async_smem();
      stW(dB, 5, 1, 4);
      bar_sync(1 + wg, 128);
      stO(dB, 0, 5);
    }
    stW(dA, 0, 0, 6);
    epiP(dB, 0);
    TSC(19);
    auto ldp = [&](uint32_t (&v)[16], const int s) {
      const uint4* src = g_part + (size_t)((r * 9 + j) * 8 + ((j - 1 - s) & 7)) * 1024 + warp * 128 + lane;
#pragma unroll
      for (int i = 0; i < 4; i++) ld_b128(v[4 * i], v[4 * i + 1], v[4 * i + 2], v[4 * i + 3], src + i * 32);
    };
    auto chk = [&](uint32_t (&v)[16], const int s) {
      uint32_t n = 0;
      while (__any_sync(0xffffffffu, (((v[0] ^ tag) | (v[4] ^ tag) | (v[8] ^ tag) | (v[12] ^ tag)) & 0x10000u) != 0)) {
        ldp(v, s);
        if (++n > SPIN_LIMIT) asm volatile("trap;");
      }
    };
    const uint32_t acc = hl + ACC;
    auto accp = [&](uint32_t (&v)[16], const int i) {
      uint32_t f[8];
      lds128(f[0], f[1], f[2], f[3], acc + i * 4096);
      lds128(f[4], f[5], f[6], f[7], acc + i * 4096 + 2048);
      auto U = [](float x) { return __float_as_uint(x); };
      auto F = [](uint32_t x) { return __uint_as_float(x); };
      sts128(acc + i * 4096, U(F(f[0]) + blo(v[4 * i])), U(F(f[1]) + F(v[4 * i] & 0xfffe0000u)), U(F(f[2]) + blo(v[4 * i + 1])), U(F(f[3]) + bhi(v[4 * i + 1])));
      sts128(acc + i * 4096 + 2048, U(F(f[4]) + blo(v[4 * i + 2])), U(F(f[5]) + bhi(v[4 * i + 2])), U(F(f[6]) + blo(v[4 * i + 3])), U(F(f[7]) + bhi(v[4 * i + 3])));
    };
    {
      uint32_t v[16];
      const uint32_t* xp = reinterpret_cast<const uint32_t*>(p.x + (size_t)(r * 128 + warp * 16 + (lane >> 2)) * D_ + 64 * j + 2 * (lane & 3));
      stW(dA, 1, 0, 0);
#pragma unroll
      for (int t = 0; t < 8; t++) { v[2 * t] = __ldg(xp + 4 * t); v[2 * t + 1] = __ldg(xp + 4 * D_ + 4 * t); }
      stW(dA, 2, 0, 1);
      stW(dA, 3, 0, 2);
      stW(dA, 4, 0, 3);
      stW(dA, 5, 0, 4);
#pragma unroll
      for (int i = 0; i < 4; i++) sts128(acc + i * 2048, v[2 * i] << 16, v[2 * i] & 0xffff0000u, v[2 * i + 1] << 16, v[2 * i + 1] & 0xffff0000u);
      stO(dA, 1, 5);
#pragma unroll
      for (int i = 4; i < 8; i++) sts128(acc + i * 2048, v[2 * i] << 16, v[2 * i] & 0xffff0000u, v[2 * i + 1] << 16, v[2 * i + 1] & 0xffff0000u);
      stW(dB, 0, 1, 6);
      epiP(dA, 1);
    }
    TSC(20);
#pragma unroll 1
    for (int it = 0; it < 3; it++) {
      uint32_t v[16];
      if (it > 0) ldp(v, 2 * it - 1);
      stW(dB, 1, 1, 0);
      stW(dB, 2, 1, 1);
      stW(dB, 3, 1, 2);
      if (it > 0) { chk(v, 2 * it - 1); accp(v, 0); }
      stW(dB, 4, 1, 3);
      if (it > 0) accp(v, 1);
      stW(dB, 5, 1, 4);
      if (it > 0) accp(v, 2);
      stO(dB, 0, 5);
      if (it > 0) accp(v, 3);
      stW(dA, 0, 0, 6);
      epiP(dB, 2 + 2 * it);
      ldp(v, 2 * it);
      stW(dA, 1, 0, 0);
      stW(dA, 2, 0, 1);
      stW(dA, 3, 0, 2);
      chk(v, 2 * it);
      accp(v, 0);
      stW(dA, 4, 0, 3);
      accp(v, 1);
      stW(dA, 5, 0, 4);
      accp(v, 2);
      stO(dA, 1, 5);
      accp(v, 3);
      stW(dB, 0, 1, 6);
      epiP(dA, 3 + 2 * it);
      TSC(21 + it);
    }
    {
      uint32_t v[16], w[16];
      float f[32] = {};
      auto addv = [&](uint32_t (&v)[16], const int i) {
        f[8 * i] += blo(v[4 * i]); f[8 * i + 1] += __uint_as_float(v[4 * i] & 0xfffe0000u); f[8 * i + 2] += blo(v[4 * i + 1]); f[8 * i + 3] += bhi(v[4 * i + 1]);
        f[8 * i + 4] += blo(v[4 * i + 2]); f[8 * i + 5] += bhi(v[4 * i + 2]); f[8 * i + 6] += blo(v[4 * i + 3]); f[8 * i + 7] += bhi(v[4 * i + 3]);
        pin8(f, 8 * i);
      };
      ldp(v, 5);
      stW(dB, 1, 1, -1);
      stW(dB, 2, 1, -1);
#pragma unroll
      for (int i = 0; i < 8; i++) {
        uint32_t t0, t1, t2, t3;
        lds128(t0, t1, t2, t3, acc + i * 2048);
        f[4 * i] = __uint_as_float(t0); f[4 * i + 1] = __uint_as_float(t1); f[4 * i + 2] = __uint_as_float(t2); f[4 * i + 3] = __uint_as_float(t3);
      }
      stW(dB, 3, 1, -1);
      ldp(w, 6);
      chk(v, 5);
      addv(v, 0); addv(v, 1);
      stW(dB, 4, 1, -1);
      addv(v, 2); addv(v, 3);
      stW(dB, 5, 1, -1);
      stO(dB, 0, -1);
      TSC(24);
      chk(w, 6);
      addv(w, 0); addv(w, 1); addv(w, 2); addv(w, 3);
      TSC(25);
      wg_wait<0>();
      TSC(26); GT(2);
      pin(dB);
      const uint32_t ps = sb + HB + wg * HHALF + STG + (warp & 3) * 2048;
      const int row = lane & 15;
#pragma unroll
      for (int t = 0; t < 8; t += 2)
        stsm4(ps + row * 128 + (((t + (lane >> 4)) ^ (row & 7)) << 4),
              pack2(f[4 * t] + dB[4 * t], f[4 * t + 1] + dB[4 * t + 1]), pack2(f[4 * t + 2] + dB[4 * t + 2], f[4 * t + 3] + dB[4 * t + 3]),
              pack2(f[4 * t + 4] + dB[4 * t + 4], f[4 * t + 5] + dB[4 * t + 5]), pack2(f[4 * t + 6] + dB[4 * t + 6], f[4 * t + 7] + dB[4 * t + 7]));
      __syncwarp();
#pragma unroll
      for (int i = 0; i < 4; i++) {
        const int rr = i * 4 + (lane >> 3), ch = lane & 7;
        uint4 o;
        lds128(o.x, o.y, o.z, o.w, ps + rr * 128 + ((ch ^ (rr & 7)) << 4));
        *reinterpret_cast<uint4*>(p.out + (size_t)(r * 128 + warp * 16 + rr) * D_ + 64 * j + ch * 8) = o;
      }
    }
    TSC(27); GT(3);
  }
}

typedef CUresult (*EncodeFn)(CUtensorMap*, CUtensorMapDataType, cuuint32_t, void*, const cuuint64_t*, const cuuint64_t*, const cuuint32_t*,
                             const cuuint32_t*, CUtensorMapInterleave, CUtensorMapSwizzle, CUtensorMapL2promotion, CUtensorMapFloatOOBfill);

CUtensorMap make_map(EncodeFn enc, const void* ptr, int rows, int cols, int brow, int bcol, CUtensorMapSwizzle sw) {
  CUtensorMap m;
  cuuint64_t gd[2] = {(cuuint64_t)cols, (cuuint64_t)rows};
  cuuint64_t gs[1] = {(cuuint64_t)cols * 2};
  cuuint32_t bd[2] = {(cuuint32_t)bcol, (cuuint32_t)brow};
  cuuint32_t es[2] = {1, 1};
  enc(&m, CU_TENSOR_MAP_DATA_TYPE_BFLOAT16, 2, const_cast<void*>(ptr), gd, gs, bd, es, CU_TENSOR_MAP_INTERLEAVE_NONE, sw,
      CU_TENSOR_MAP_L2_PROMOTION_L2_128B, CU_TENSOR_MAP_FLOAT_OOB_FILL_NONE);
  return m;
}

}

extern "C" void kernel_launch(void* const* d_in, const int* in_sizes, int n_in, void* d_out, int out_size) {
  (void)in_sizes; (void)n_in; (void)out_size;
  static EncodeFn enc = nullptr;
  static void* m_ptr = nullptr;
  if (!enc) {
    cudaGetSymbolAddress(&m_ptr, g_M);
    cudaDriverEntryPointQueryResult qr;
    cudaGetDriverEntryPoint("cuTensorMapEncodeTiled", (void**)&enc, cudaEnableDefault, &qr);
    cudaFuncSetAttribute(fused_block_kernel, cudaFuncAttributeMaxDynamicSharedMemorySize, SMEM_BYTES);
  }
  Params p;
  p.x = (const __nv_bfloat16*)d_in[0];
  p.wqkv = (const __nv_bfloat16*)d_in[1];
  p.wo = (const __nv_bfloat16*)d_in[2];
  p.w1 = (const __nv_bfloat16*)d_in[4];
  p.w3 = (const __nv_bfloat16*)d_in[5];
  p.w2 = (const __nv_bfloat16*)d_in[6];
  p.out = (__nv_bfloat16*)d_out;
  const CUtensorMap m_qkv = make_map(enc, p.wqkv, D_, 3 * D_, 96, 64, CU_TENSOR_MAP_SWIZZLE_128B);
  const CUtensorMap m_w1 = make_map(enc, p.w1, D_, F_, 96, 32, CU_TENSOR_MAP_SWIZZLE_64B);
  const CUtensorMap m_w3 = make_map(enc, p.w3, D_, F_, 96, 32, CU_TENSOR_MAP_SWIZZLE_64B);
  const CUtensorMap m_w2 = make_map(enc, p.w2, F_, D_, 96, 64, CU_TENSOR_MAP_SWIZZLE_128B);
  const CUtensorMap m_M = make_map(enc, m_ptr, 8 * 80, D_, 80, 64, CU_TENSOR_MAP_SWIZZLE_128B);
  const CUtensorMap m_x = make_map(enc, p.x, 2048, D_, 128, 64, CU_TENSOR_MAP_SWIZZLE_128B);
  fused_block_kernel<<<128, NTHREADS, SMEM_BYTES>>>(m_qkv, m_w1, m_w3, m_w2, m_M, m_x, p);
}
```

```cpp
#include <cuda_runtime.h>
#include <cuda.h>
#include <cuda_bf16.h>
#include <stdint.h>

namespace {

constexpr int D_ = 576, F_ = 4608;
constexpr int NTHREADS = 384;

constexpr uint32_t SLOT = 12288;
constexpr uint32_t HB = 6 * SLOT;
constexpr uint32_t HHALF = 73728;
constexpr uint32_t PK_T = HB + 45056;
constexpr uint32_t V_T = HB + HHALF + 18432;
constexpr uint32_t L24_T = HB + 16384;
constexpr uint32_t WO_SLOT = HB + 12288;
constexpr uint32_t STG = 49152;
constexpr uint32_t Q8 = HB + 2 * HHALF;
constexpr uint32_t WOB = Q8 + 2048;
constexpr uint32_t KVS = WOB + 5184;
constexpr uint32_t ZM = WOB;
constexpr uint32_t TAGW = KVS + 1440;
constexpr uint32_t BARS = TAGW + 32;
constexpr uint32_t SMEM_BYTES = BARS + 512;

constexpr uint32_t B_X = BARS;
constexpr uint32_t B_FULL = BARS + 8 * 9;
constexpr uint32_t B_EMPTY = BARS + 8 * 16;
constexpr uint32_t B_XDONE = BARS + 8 * 23;
constexpr uint32_t B_KVT = BARS + 8 * 24;
constexpr uint32_t B_KVD = BARS + 8 * 25;
constexpr uint32_t B_HFREE = BARS + 8 * 26;
constexpr uint32_t B_LFULL = BARS + 8 * 27;
constexpr uint32_t B_MRDY = BARS + 8 * 28;

#define WDELAY 2
#define XWAIT 8
constexpr uint32_t SPIN_LIMIT = 1u << 22;

__device__ uint4 g_part[16 * 9 * 8 * 1024];
__device__ float4 g_kvp[8 * 16 * 1280];
__device__ __align__(128) __nv_bfloat16 g_M[8 * 80 * 576];
__device__ __align__(16) float g_z[8 * 72];
__device__ uint32_t g_cnt1[8 * 32], g_cnt2[8 * 32];
__device__ uint32_t g_epoch[128];

#define TS(slot, i)
#define TSC(i)
#define GT(i)

__device__ __forceinline__ void wg_fence() { asm volatile("wgmma.fence.sync.aligned;\n" ::: "memory"); }
__device__ __forceinline__ void wg_commit() { asm volatile("wgmma.commit_group.sync.aligned;\n" ::: "memory"); }
template <int N> __device__ __forceinline__ void wg_wait() { asm volatile("wgmma.wait_group.sync.aligned %0;\n" ::"n"(N) : "memory"); }
__host__ __device__ constexpr uint64_t mkdesc(uint32_t addr, uint32_t lbo, uint32_t sbo, uint32_t sw) {
  return (uint64_t)((addr & 0x3FFFF) >> 4) | ((uint64_t)(lbo >> 4) << 16) | ((uint64_t)(sbo >> 4) << 32) | ((uint64_t)sw << 62);
}
__device__ __forceinline__ void mbar_init(uint32_t a, uint32_t c) { asm volatile("mbarrier.init.shared::cta.b64 [%0], %1;\n" ::"r"(a), "r"(c) : "memory"); }
__device__ __forceinline__ void mbar_expect(uint32_t a, uint32_t b) { asm volatile("mbarrier.arrive.expect_tx.shared::cta.b64 _, [%0], %1;\n" ::"r"(a), "r"(b) : "memory"); }
__device__ __forceinline__ void mbar_arrive(uint32_t a) { asm volatile("mbarrier.arrive.shared::cta.b64 _, [%0];\n" ::"r"(a) : "memory"); }
__device__ __forceinline__ void mbar_wait(uint32_t a, uint32_t ph) {
  asm volatile(
      "{\n.reg .pred p;\n.reg .u32 n;\n"
      "mov.u32 n, 0;\n"
      "LOOP:\n"
      "mbarrier.try_wait.parity.shared::cta.b64 p, [%0], %1;\n"
      "@p bra DONE;\n"
      "add.u32 n, n, 1;\n"
      "setp.gt.u32 p, n, %2;\n"
      "@p trap;\n"
      "bra LOOP;\n"
      "DONE:\n}\n" ::"r"(a), "r"(ph), "n"(SPIN_LIMIT) : "memory");
}
__device__ __forceinline__ void cp_async16(uint32_t dst, const void* src) {
  asm volatile("cp.async.cg.shared.global [%0], [%1], 16;\n" ::"r"(dst), "l"(src) : "memory");
}
__device__ __forceinline__ void tma2d(uint32_t dst, const CUtensorMap* m, int c0, int c1, uint32_t bar) {
  asm volatile("cp.async.bulk.tensor.2d.shared::cluster.global.mbarrier::complete_tx::bytes [%0], [%1, {%3, %4}], [%2];\n" ::"r"(dst), "l"(m), "r"(bar), "r"(c0), "r"(c1) : "memory");
}
__device__ __forceinline__ void tma2d_prefetch(const CUtensorMap* m, int c0, int c1) {
  asm volatile("cp.async.bulk.prefetch.tensor.2d.L2.global [%0, {%1, %2}];\n" ::"l"(m), "r"(c0), "r"(c1) : "memory");
}
__device__ __forceinline__ void fence_async_smem() { asm volatile("fence.proxy.async.shared::cta;\n" ::: "memory"); }
__device__ __forceinline__ void bar_sync(int id, int n) { asm volatile("bar.sync %0, %1;\n" ::"r"(id), "r"(n) : "memory"); }
__device__ __forceinline__ void ldsm4(uint32_t& r0, uint32_t& r1, uint32_t& r2, uint32_t& r3, uint32_t a) {
  asm volatile("ldmatrix.sync.aligned.m8n8.x4.shared.b16 {%0,%1,%2,%3}, [%4];\n" : "=r"(r0), "=r"(r1), "=r"(r2), "=r"(r3) : "r"(a) : "memory");
}
__device__ __forceinline__ void stsm4(uint32_t a, uint32_t r0, uint32_t r1, uint32_t r2, uint32_t r3) {
  asm volatile("stmatrix.sync.aligned.m8n8.x4.shared.b16 [%0], {%1,%2,%3,%4};\n" ::"r"(a), "r"(r0), "r"(r1), "r"(r2), "r"(r3) : "memory");
}
__device__ __forceinline__ void sts128(uint32_t a, uint32_t r0, uint32_t r1, uint32_t r2, uint32_t r3) {
  asm volatile("st.shared.v4.b32 [%0], {%1,%2,%3,%4};\n" ::"r"(a), "r"(r0), "r"(r1), "r"(r2), "r"(r3) : "memory");
}
__device__ __forceinline__ void lds128(uint32_t& r0, uint32_t& r1, uint32_t& r2, uint32_t& r3, uint32_t a) {
  asm volatile("ld.shared.v4.b32 {%0,%1,%2,%3}, [%4];\n" : "=r"(r0), "=r"(r1), "=r"(r2), "=r"(r3) : "r"(a) : "memory");
}
template <int OFF>
__device__ __forceinline__ void lds128_inplace(uint32_t (&r)[4], uint32_t a) {
  asm volatile("{\n.reg .pred p;\nsetp.ne.u32 p, %4, 0;\n@p ld.shared.v4.b32 {%0,%1,%2,%3}, [%4 + %5];\n}\n"
               : "+r"(r[0]), "+r"(r[1]), "+r"(r[2]), "+r"(r[3]) : "r"(a), "n"(OFF) : "memory");
}
__device__ __forceinline__ void sts64(uint32_t a, uint32_t r0, uint32_t r1) { asm volatile("st.shared.v2.b32 [%0], {%1,%2};\n" ::"r"(a), "r"(r0), "r"(r1) : "memory"); }
__device__ __forceinline__ void lds64(uint32_t& r0, uint32_t& r1, uint32_t a) { asm volatile("ld.shared.v2.b32 {%0,%1}, [%2];\n" : "=r"(r0), "=r"(r1) : "r"(a) : "memory"); }
__device__ __forceinline__ uint32_t lds32(uint32_t a) { uint32_t v; asm volatile("ld.shared.b32 %0, [%1];\n" : "=r"(v) : "r"(a) : "memory"); return v; }
__device__ __forceinline__ void sts32(uint32_t a, uint32_t r0) { asm volatile("st.shared.b32 [%0], %1;\n" ::"r"(a), "r"(r0) : "memory"); }
__device__ __forceinline__ void mma16816(float (&c)[4], uint32_t a0, uint32_t a1, uint32_t a2, uint32_t a3, uint32_t b0, uint32_t b1) {
  asm volatile("mma.sync.aligned.m16n8k16.row.col.f32.bf16.bf16.f32 {%0,%1,%2,%3}, {%4,%5,%6,%7}, {%8,%9}, {%0,%1,%2,%3};\n"
               : "+f"(c[0]), "+f"(c[1]), "+f"(c[2]), "+f"(c[3]) : "r"(a0), "r"(a1), "r"(a2), "r"(a3), "r"(b0), "r"(b1));
}
__device__ __forceinline__ void mma1688(float (&c)[4], uint32_t a0, uint32_t a1, uint32_t b0) {
  asm volatile("mma.sync.aligned.m16n8k8.row.col.f32.bf16.bf16.f32 {%0,%1,%2,%3}, {%4,%5}, {%6}, {%0,%1,%2,%3};\n"
               : "+f"(c[0]), "+f"(c[1]), "+f"(c[2]), "+f"(c[3]) : "r"(a0), "r"(a1), "r"(b0));
}
__device__ __forceinline__ uint32_t pack2(float lo, float hi) {
  uint32_t r;
  asm("cvt.rn.bf16x2.f32 %0, %1, %2;\n" : "=r"(r) : "f"(hi), "f"(lo));
  return r;
}
__device__ __forceinline__ float blo(uint32_t w) { return __uint_as_float(w << 16); }
__device__ __forceinline__ float bhi(uint32_t w) { return __uint_as_float(w & 0xffff0000u); }
__device__ __forceinline__ float rbf(float x) { return __bfloat162float(__float2bfloat16_rn(x)); }
__device__ __forceinline__ float ex2(float x) { float r; asm("ex2.approx.ftz.f32 %0, %1;\n" : "=f"(r) : "f"(x)); return r; }
__device__ __forceinline__ float rcp(float x) { float r; asm("rcp.approx.ftz.f32 %0, %1;\n" : "=f"(r) : "f"(x)); return r; }
__device__ __forceinline__ float sqrta(float x) { float r; asm("sqrt.approx.ftz.f32 %0, %1;\n" : "=f"(r) : "f"(x)); return r; }
__device__ __forceinline__ uint32_t bsub2(uint32_t a, uint32_t b) { uint32_t r; asm("sub.rn.bf16x2 %0, %1, %2;\n" : "=r"(r) : "r"(a), "r"(b)); return r; }
__device__ __forceinline__ uint32_t ld_acq(const uint32_t* p) { uint32_t v; asm volatile("ld.acquire.gpu.global.u32 %0, [%1];\n" : "=r"(v) : "l"(p) : "memory"); return v; }
__device__ __forceinline__ void st_b128(void* p, uint32_t a, uint32_t b, uint32_t c, uint32_t d) {
  asm volatile("st.relaxed.gpu.global.v4.b32 [%0], {%1, %2, %3, %4};\n" ::"l"(p), "r"(a), "r"(b), "r"(c), "r"(d) : "memory");
}
__device__ __forceinline__ void ld_b128(uint32_t& a, uint32_t& b, uint32_t& c, uint32_t& d, const void* p) {
  asm volatile("{\n.reg .b128 v;\nld.relaxed.gpu.global.b128 v, [%4];\nmov.b128 {%0, %1, %2, %3}, v;\n}\n" : "=r"(a), "=r"(b), "=r"(c), "=r"(d) : "l"(p) : "memory");
}
__device__ __forceinline__ bool elect_one() {
  uint32_t ok;
  asm volatile("{\n.reg .pred p;\nelect.sync _|p, 0xffffffff;\nselp.u32 %0, 1, 0, p;\n}\n" : "=r"(ok));
  return ok;
}
__device__ __forceinline__ uint32_t bmul2(uint32_t a, uint32_t b) { uint32_t r; asm("mul.rn.bf16x2 %0, %1, %2;\n" : "=r"(r) : "r"(a), "r"(b)); return r; }
__device__ __forceinline__ void red_rel(uint32_t* p) { asm volatile("red.release.gpu.global.add.u32 [%0], 1;\n" ::"l"(p) : "memory"); }
__device__ __forceinline__ void wait_ge(const uint32_t* p, uint32_t target) {
  uint32_t n = 0;
  while ((int32_t)(ld_acq(p) - target) < 0) {
    __nanosleep(64);
    if (++n > SPIN_LIMIT) __trap();
  }
}
__device__ __forceinline__ float phi(float a, float r, float rl) { return fmaf(fmaxf(a, 0.f), r, __saturatef(ex2(a * rl) + 1e-6f)); }

#define ACC8(d, o) "+f"(d[o + 0]), "+f"(d[o + 1]), "+f"(d[o + 2]), "+f"(d[o + 3]), "+f"(d[o + 4]), "+f"(d[o + 5]), "+f"(d[o + 6]), "+f"(d[o + 7])
#define REGS32 "{%0,%1,%2,%3,%4,%5,%6,%7,%8,%9,%10,%11,%12,%13,%14,%15,%16,%17,%18,%19,%20,%21,%22,%23,%24,%25,%26,%27,%28,%29,%30,%31}"
__device__ __forceinline__ void wgmma_rs64(float (&d)[32], const uint32_t (&a)[4], uint64_t db, int acc) {
  asm volatile("{\n.reg .pred p;\nsetp.ne.b32 p, %37, 0;\n"
               "wgmma.mma_async.sync.aligned.m64n64k16.f32.bf16.bf16 " REGS32 ", {%32,%33,%34,%35}, %36, p, 1, 1, 1;\n}\n"
               : ACC8(d, 0), ACC8(d, 8), ACC8(d, 16), ACC8(d, 24)
               : "r"(a[0]), "r"(a[1]), "r"(a[2]), "r"(a[3]), "l"(db), "r"(acc));
}
template <uint32_t OFF, uint32_t HI>
__device__ __forceinline__ void wgmma_ss64(float (&d)[32], uint32_t da_lo, uint64_t db) {
  asm volatile("{\n.reg .b32 lo;\n.reg .b64 da;\nadd.u32 lo, %32, %34;\nmov.b64 da, {lo, %35};\n"
               "wgmma.mma_async.sync.aligned.m64n64k16.f32.bf16.bf16 " REGS32 ", da, %33, 1, 1, 1, 0, 1;\n}\n"
               : ACC8(d, 0), ACC8(d, 8), ACC8(d, 16), ACC8(d, 24)
               : "r"(da_lo), "l"(db), "n"(OFF), "n"(HI));
}
__device__ __forceinline__ void wgmma_rs24(float (&d)[12], const uint32_t (&a)[4], uint64_t db, int acc) {
  asm volatile("{\n.reg .pred p;\nsetp.ne.b32 p, %17, 0;\n"
               "wgmma.mma_async.sync.aligned.m64n24k16.f32.bf16.bf16 {%0,%1,%2,%3,%4,%5,%6,%7,%8,%9,%10,%11}, {%12,%13,%14,%15}, %16, p, 1, 1, 1;\n}\n"
               : ACC8(d, 0), "+f"(d[8]), "+f"(d[9]), "+f"(d[10]), "+f"(d[11])
               : "r"(a[0]), "r"(a[1]), "r"(a[2]), "r"(a[3]), "l"(db), "r"(acc));
}
__device__ __forceinline__ void wgmma_ss40tt(float (&d)[20], uint64_t da, uint64_t db, int acc) {
  asm volatile("{\n.reg .pred p;\nsetp.ne.b32 p, %22, 0;\n"
               "wgmma.mma_async.sync.aligned.m64n40k16.f32.bf16.bf16 {%0,%1,%2,%3,%4,%5,%6,%7,%8,%9,%10,%11,%12,%13,%14,%15,%16,%17,%18,%19}, %20, %21, p, 1, 1, 1, 1;\n}\n"
               : ACC8(d, 0), ACC8(d, 8), "+f"(d[16]), "+f"(d[17]), "+f"(d[18]), "+f"(d[19])
               : "l"(da), "l"(db), "r"(acc));
}
template <uint32_t OFF, uint32_t HI, int ACCUM>
__device__ __forceinline__ void wgmma_ss16(float (&d)[8], uint32_t da_lo, uint64_t db) {
  asm volatile("{\n.reg .b32 lo;\n.reg .b64 da;\n.reg .pred p;\nsetp.ne.b32 p, %12, 0;\nadd.u32 lo, %8, %10;\nmov.b64 da, {lo, %11};\n"
               "wgmma.mma_async.sync.aligned.m64n16k16.f32.bf16.bf16 {%0,%1,%2,%3,%4,%5,%6,%7}, da, %9, p, 1, 1, 0, 1;\n}\n"
               : ACC8(d, 0)
               : "r"(da_lo), "l"(db), "n"(OFF), "n"(HI), "n"(ACCUM));
}
template <int N> __device__ __forceinline__ void pin(float (&d)[N]) {
#pragma unroll
  for (int i = 0; i < N; i++) asm volatile("" : "+f"(d[i])::"memory");
}

__device__ __forceinline__ void pin8(float (&d)[32], const int o) { asm volatile("" : ACC8(d, o)::"memory"); }

template <int I> struct IC { static constexpr int value = I; };
template <int I, int N, class F> __device__ __forceinline__ void static_for(F f) {
  if constexpr (I < N) { f(IC<I>()); static_for<I + 1, N>(f); }
}

struct Params {
  const __nv_bfloat16* x;
  const __nv_bfloat16* wqkv;
  const __nv_bfloat16* wo;
  const __nv_bfloat16* w1;
  const __nv_bfloat16* w3;
  const __nv_bfloat16* w2;
  __nv_bfloat16* out;
};

__global__ void __launch_bounds__(NTHREADS, 1)
fused_block_kernel(const __grid_constant__ CUtensorMap m_qkv, const __grid_constant__ CUtensorMap m_w1,
                   const __grid_constant__ CUtensorMap m_w3, const __grid_constant__ CUtensorMap m_w2,
                   const __grid_constant__ CUtensorMap m_M, const __grid_constant__ CUtensorMap m_x, const Params p) {
  extern __shared__ __align__(1024) uint8_t smem_raw[];
  constexpr uint32_t sb = 1024;
  if ((uint32_t)__cvta_generic_to_shared(smem_raw) != sb) __trap();
  const int tid = threadIdx.x, warp = __shfl_sync(0xffffffffu, tid >> 5, 0), lane = tid & 31;
  const int r = blockIdx.x >> 3, j = blockIdx.x & 7;

  GT(0); TSC(0);
  const int cmain = 72 * j + 8 * (j & 1);
  if (__builtin_expect(warp >= 8, 1)) {
    asm volatile("setmaxnreg.dec.sync.aligned.u32 24;\n");
    if (__builtin_expect(warp == 8, 1)) {
      if (elect_one()) {
#pragma unroll
        for (int b = 0; b < 9; b++) mbar_init(sb + B_X + 8 * b, 1);
        asm volatile("fence.mbarrier_init.release.cluster;\n" ::: "memory");
        mbar_expect(sb + B_X, 16384);
        tma2d(sb + HB, &m_x, 0, 128 * r, sb + B_X);
      }
      __syncwarp();
      asm volatile("bar.arrive 0, 384;\n" ::: "memory");
      if (elect_one()) {
#pragma unroll
        for (int b = 1; b < 9; b++) {
          mbar_expect(sb + B_X + 8 * b, 16384);
          tma2d(sb + HB + b * 16384, &m_x, 64 * b, 128 * r, sb + B_X + 8 * b);
        }
      }
      __syncwarp();
      asm volatile("bar.sync 4, 64;\n" ::: "memory");
      if (elect_one()) {
#pragma unroll
        for (int s = 0; s < 6; s++) {
          if (s == WDELAY) mbar_wait(sb + B_X + 8 * XWAIT, 0);
          mbar_expect(sb + B_FULL + 8 * s, SLOT);
          tma2d(sb + s * SLOT, &m_qkv, D_ + cmain, 96 * s, sb + B_FULL + 8 * s);
        }
        const CUtensorMap* mpf = (r & 1) ? &m_w3 : &m_w1;
        if (r < 6) tma2d_prefetch(&m_qkv, 2 * D_ + cmain, 96 * r);
        if (r < 12) { tma2d_prefetch(mpf, 576 * j, 96 * (r >> 1)); tma2d_prefetch(mpf, 576 * j + 32, 96 * (r >> 1)); }
#pragma unroll
        for (int s = 0; s < 6; s++) {
          mbar_wait(sb + B_EMPTY + 8 * s, 0);
          mbar_expect(sb + B_FULL + 8 * s, SLOT);
          tma2d(sb + s * SLOT, &m_qkv, 2 * D_ + cmain, 96 * s, sb + B_FULL + 8 * s);
        }
#pragma unroll 1
        for (int n = 0; n < 18; n++) {
          const int col = 576 * j + 32 * n;
          if (n < 16) { if (r < 12) tma2d_prefetch(mpf, col + 64, 96 * (r >> 1)); }
          else if (r < 6) {
            if (n == 16) tma2d_prefetch(&m_qkv, cmain, 96 * r);
            else tma2d_prefetch(&m_w2, 512, 576 * j + 96 * r);
          }
#pragma unroll
          for (int s = 0; s < 6; s++) {
            mbar_wait(sb + B_EMPTY + 8 * s, (n & 1) ^ 1);
            mbar_expect(sb + B_FULL + 8 * s, SLOT);
            tma2d(sb + s * SLOT, &m_w1, col, 96 * s, sb + B_FULL + 8 * s);
            tma2d(sb + s * SLOT + SLOT / 2, &m_w3, col, 96 * s, sb + B_FULL + 8 * s);
          }
        }
        if (r < 6) tma2d_prefetch(&m_w2, 64 * ((j + 1) & 7), 576 * j + 96 * r);
#pragma unroll
        for (int s = 0; s < 6; s++) {
          mbar_wait(sb + B_EMPTY + 8 * s, 1);
          mbar_expect(sb + B_FULL + 8 * s, SLOT);
          tma2d(sb + s * SLOT, &m_qkv, cmain, 96 * s, sb + B_FULL + 8 * s);
        }
#pragma unroll 1
        for (int n = 0; n < 9; n++) {
          const int col = n == 0 ? 512 : 64 * ((j + n) & 7);
          if (n < 7 && r < 6) tma2d_prefetch(&m_w2, 64 * ((j + n + 2) & 7), 576 * j + 96 * r);
#pragma unroll
          for (int s = 0; s < 6; s++) {
            mbar_wait(sb + B_EMPTY + 8 * s, n & 1);
            mbar_expect(sb + B_FULL + 8 * s, SLOT);
            tma2d(sb + s * SLOT, &m_w2, col, 576 * j + 96 * s, sb + B_FULL + 8 * s);
          }
          if (n == 0) {
            mbar_wait(sb + B_HFREE, 0);
            mbar_wait(sb + B_MRDY, 0);
            asm volatile("fence.proxy.async;\n" ::: "memory");
          }
          mbar_wait(sb + B_EMPTY + 48, (n & 1) ^ 1);
          mbar_expect(sb + B_FULL + 48, 80 * 128);
          tma2d(sb + WO_SLOT, &m_M, col, 80 * j, sb + B_FULL + 48);
        }
      }
    } else {
      const int ht = tid - 288;
      if (warp == 9) {
        if (elect_one()) {
          asm volatile("prefetch.tensormap [%0];\n" ::"l"(&m_qkv) : "memory");
#pragma unroll
          for (int i = 9; i < 29; i++) mbar_init(sb + BARS + 8 * i, i < 16 ? 1 : i < 26 ? 8 : i == 26 ? 4 : 96);
          asm volatile("fence.mbarrier_init.release.cluster;\n" ::: "memory");
        }
        __syncwarp();
        asm volatile("bar.arrive 4, 64;\n" ::: "memory");
      }
      asm volatile("bar.sync 0, 384;\n" ::: "memory");
      const uint32_t ep = g_epoch[blockIdx.x] + 1;
      mbar_wait(sb + B_X + 8 * 8, 0);
      if (ht < 90) {
        const int e = ht / 18, c = ht - e * 18;
        const __nv_bfloat16* w = p.wo + (size_t)(72 * j + 18 * (r >> 2) + e) * D_ + 144 * (r & 3) + c * 8;
#pragma unroll
        for (int i = 0; i < 4; i++)
          if (i < 3 || ht < 54) cp_async16(sb + WOB + ht * 16 + i * 90 * 16, w + i * 5 * D_);
      }
      const __nv_bfloat16* wl = p.wqkv + (size_t)ht * (3 * D_) + 72 * j + ((j & 1) ? 0 : 64);
      mbar_wait(sb + B_XDONE, 0);
#pragma unroll
      for (int g = 0; g < 3; g++)
#pragma unroll
        for (int m = 0; m < 6; m++) cp_async16(sb + L24_T + g * 9216 + m * 96 * 16 + ht * 16, wl + (size_t)m * 96 * 3 * D_ + (g == 2 ? 0 : (g + 1) * D_));
      if (ht < 64) {
#pragma unroll
        for (int i = 0; i < 4; i++) sts128(sb + V_T - 2048 + (i >> 1) * 20480 + (i & 1) * 1024 + ht * 16, 0x3F803F80u, 0x3F803F80u, 0x3F803F80u, 0x3F803F80u);
      }
      asm volatile("cp.async.wait_all;\n" ::: "memory");
      fence_async_smem();
      mbar_arrive(sb + B_LFULL);
      if (warp == 9) TS(3, 1);

      if (ht == 0) {
        mbar_wait(sb + B_KVD, 0);
        red_rel(&g_cnt1[j * 32]);
        wait_ge(&g_cnt1[j * 32], 16 * ep);
      }
      bar_sync(3, 96);
      if (warp == 9) TS(3, 4);
#pragma unroll 1
      for (int i = ht; i < 171; i += 96) {
        const int dp = i / 19, el = i - dp * 19, hd = r >> 2, w = hd >> 1;
        const int d = 18 * hd + 2 * dp - 32 * w;
        const int m = el == 18 ? 56 * w : 18 * hd + el + 8 - 24 * w;
        const float2* src = reinterpret_cast<const float2*>(g_kvp + j * 16 * 1280 + ((w * 4 + (m >> 4)) * 5 + (d >> 3)) * 32 + (m & 7) * 4 + ((d & 7) >> 1)) + ((m >> 3) & 1);
        float s0 = 0.f, s1 = 0.f;
#pragma unroll 1
        for (int r4 = 0; r4 < 4; r4++) {
          const float2 v0 = __ldcg(src), v1 = __ldcg(src + 2560), v2 = __ldcg(src + 2 * 2560), v3 = __ldcg(src + 3 * 2560);
          s0 += (v0.x + v1.x) + (v2.x + v3.x);
          s1 += (v0.y + v1.y) + (v2.y + v3.y);
          src += 4 * 2560;
        }
        sts64(sb + KVS + dp * 160 + el * 8, __float_as_uint(s0), __float_as_uint(s1));
        if ((r & 3) == 0 && el == 18) *reinterpret_cast<float2*>(g_z + j * 72 + hd * 18 + dp * 2) = make_float2(s0, s1);
      }
      bar_sync(3, 96);
      if (warp == 9) TS(3, 5);
#pragma unroll 1
      for (int t = ht; t < 648; t += 96) {
        const int dp = t / 72, cp = t - dp * 72;
        float c0 = 0.f, c1 = 0.f, c2 = 0.f, c3 = 0.f;
        const uint32_t ka = sb + KVS + dp * 160, wa = sb + WOB + cp * 4;
#pragma unroll
        for (int e2 = 0; e2 < 9; e2++) {
          uint32_t a0, a1, a2, a3;
          lds128(a0, a1, a2, a3, ka + e2 * 16);
          const uint32_t w0 = lds32(wa + e2 * 576), w1 = lds32(wa + e2 * 576 + 288);
          c0 = fmaf(__uint_as_float(a0), blo(w0), c0); c1 = fmaf(__uint_as_float(a0), bhi(w0), c1);
          c2 = fmaf(__uint_as_float(a1), blo(w0), c2); c3 = fmaf(__uint_as_float(a1), bhi(w0), c3);
          c0 = fmaf(__uint_as_float(a2), blo(w1), c0); c1 = fmaf(__uint_as_float(a2), bhi(w1), c1);
          c2 = fmaf(__uint_as_float(a3), blo(w1), c2); c3 = fmaf(__uint_as_float(a3), bhi(w1), c3);
        }
        const int d = 18 * (r >> 2) + 2 * dp;
        uint32_t* dst = reinterpret_cast<uint32_t*>(g_M) + (80 * j + ((j & 1) ? (d < 8 ? d + 64 : d - 8) : d)) * 288 + 72 * (r & 3) + cp;
        dst[0] = pack2(c0, c1);
        dst[288] = pack2(c2, c3);
      }
      asm volatile("fence.proxy.async;\n" ::: "memory");
      bar_sync(3, 96);
      if (warp == 9) TS(3, 6);
      if (ht == 0) { red_rel(&g_cnt2[j * 32]); wait_ge(&g_cnt2[j * 32], 16 * ep); }
      bar_sync(3, 96);
      if (ht < 80) {
        const int d = (j & 1) ? (ht < 64 ? ht + 8 : ht - 64) : ht;
        uint32_t zb = 0;
        if (ht < 72) zb = pack2(__ldcg(g_z + j * 72 + d), 0.f);
        const int hd = d / 18;
        const uint32_t w = (hd & 1) ? zb << 16 : zb;
        const uint32_t w0 = hd < 2 ? w : 0u, w1 = hd < 2 ? 0u : w;
        sts128(sb + ZM + ht * 16, w0, w0, w0, w0);
        sts128(sb + ZM + 1280 + ht * 16, w1, w1, w1, w1);
      }
      const uint32_t tag = (ep & 1) << 16;
      if (ht == 95) { sts32(sb + TAGW, tag); g_epoch[blockIdx.x] = ep; }
      fence_async_smem();
      mbar_arrive(sb + B_MRDY);
      if (warp == 9) TS(3, 7);
      if (warp < 11) {
        mbar_wait(sb + B_FULL + 48, 0);
#pragma unroll 1
        for (int i = warp - 9; i < 4; i += 2) {
          const uint4* src = g_part + (size_t)((r * 9 + 8) * 8) * 1024 + j * 128 + i * 32 + lane;
          const int off = ((r * 128 + j * 16 + (lane >> 2)) * D_ + 512 + 16 * i + 2 * (lane & 3)) >> 1;
          float s0, s1, s2, s3, s4, s5, s6, s7;
          {
            const uint32_t* xp = reinterpret_cast<const uint32_t*>(p.x) + off;
            const uint32_t x0 = __ldg(xp), x1 = __ldg(xp + 4 * D_), x2 = __ldg(xp + 4), x3 = __ldg(xp + 4 * D_ + 4);
            s0 = blo(x0); s1 = bhi(x0); s2 = blo(x1); s3 = bhi(x1); s4 = blo(x2); s5 = bhi(x2); s6 = blo(x3); s7 = bhi(x3);
          }
          uint32_t n = 0;
#pragma unroll 1
          for (int jj = 0; jj < 8;) {
            uint32_t v0, v1, v2, v3;
            ld_b128(v0, v1, v2, v3, src);
            if (__all_sync(0xffffffffu, ((v0 ^ tag) & 0x10000u) == 0)) {
              s0 += blo(v0); s1 += __uint_as_float(v0 & 0xfffe0000u); s2 += blo(v1); s3 += bhi(v1);
              s4 += blo(v2); s5 += bhi(v2); s6 += blo(v3); s7 += bhi(v3);
              jj++;
              src += 1024;
            } else {
              __nanosleep(200);
              if (++n > SPIN_LIMIT) __trap();
            }
          }
          uint32_t* op = reinterpret_cast<uint32_t*>(p.out) + off;
          op[0] = pack2(s0, s1); op[4 * D_] = pack2(s2, s3); op[4] = pack2(s4, s5); op[4 * D_ + 4] = pack2(s6, s7);
        }
        if (warp == 9) TS(3, 10);
      }
    }
  } else {
    asm volatile("setmaxnreg.inc.sync.aligned.u32 240;\n");
    asm volatile("bar.sync 0, 384;\n" ::: "memory");
    const int wg = warp >> 2;
    uint32_t a[36][4];
    float dA[32], dB[32];
    const bool l0 = lane == 0;
    constexpr uint64_t dsw128 = mkdesc(sb, 16, 1024, 1);
    constexpr uint64_t dsw64 = mkdesc(sb, SLOT / 2, 512, 2);

    auto issue = [&](float (&d)[32], const uint64_t dbase, const int kstride, const int s, const uint32_t ph, const int init = 0) {
      mbar_wait(sb + B_FULL + 8 * s, ph);
      wg_fence();
#pragma unroll
      for (int ks = 0; ks < 6; ks++) wgmma_rs64(d, a[s * 6 + ks], dbase + ((s * SLOT + ks * kstride) >> 4), (s | ks | init) != 0);
    };
    auto finish = [&](const int rel) {
      wg_commit();
      wg_wait<1>();
      if (rel >= 0 && l0) mbar_arrive(sb + B_EMPTY + 8 * rel);
    };
    auto stW = [&](float (&d)[32], const int s, const uint32_t ph, const int rel) { issue(d, dsw128, 2048, s, ph); finish(rel); };
    auto stF = [&](float (&d)[32], const int s, const uint32_t ph, const int rel) { issue(d, dsw64, 1024, s, ph); finish(rel); };

    TSC(1);
    uint32_t mb0, mb1;
    float r0, r1;
    auto center = [&](const int g) {
#pragma unroll
      for (int ks = 6 * g; ks < 6 * g + 6; ks++) {
        a[ks][0] = bsub2(a[ks][0], mb0); a[ks][1] = bsub2(a[ks][1], mb1);
        a[ks][2] = bsub2(a[ks][2], mb0); a[ks][3] = bsub2(a[ks][3], mb1);
        asm volatile("" : "+r"(a[ks][0]), "+r"(a[ks][1]), "+r"(a[ks][2]), "+r"(a[ks][3])::"memory");
      }
    };
    {
      const uint32_t xa = sb + HB + (warp * 16 + (lane & 15)) * 128;
      const uint32_t sw = lane & 7, hi = lane >> 4;
      constexpr uint32_t ONES = 0x3F803F80u;
      float cs[2][4], cq[4][4];
#pragma unroll
      for (int i = 0; i < 4; i++) { cs[0][i] = cs[1][i] = cq[0][i] = cq[1][i] = cq[2][i] = cq[3][i] = 0.f; }
      auto gram = [&](const uint32_t (&e)[4]) {
        mma1688(cq[0], e[0], e[1], e[0]); mma1688(cq[1], e[0], e[1], e[1]);
        mma1688(cq[2], e[2], e[3], e[2]); mma1688(cq[3], e[2], e[3], e[3]);
      };
#pragma unroll
      for (int b = 0; b < 9; b++) {
        mbar_wait(sb + B_X + 8 * b, 0);
        if (b == 0 || b == 8) TSC(32 + b);
#pragma unroll
        for (int kk = 0; kk < 4; kk++) ldsm4(a[4 * b + kk][0], a[4 * b + kk][1], a[4 * b + kk][2], a[4 * b + kk][3], xa + b * 16384 + (((2 * kk + hi) ^ sw) << 4));
        if (b > 0) {
#pragma unroll
          for (int kk = 0; kk < 4; kk++) gram(a[4 * b - 4 + kk]);
        }
#pragma unroll
        for (int kk = 0; kk < 4; kk++) mma16816(cs[kk & 1], a[4 * b + kk][0], a[4 * b + kk][1], a[4 * b + kk][2], a[4 * b + kk][3], ONES, ONES);
      }
#pragma unroll
      for (int kk = 0; kk < 4; kk++) gram(a[32 + kk]);
      TSC(2);
      const float m0 = (cs[0][0] + cs[1][0]) * (1.f / 576.f), m1 = (cs[0][2] + cs[1][2]) * (1.f / 576.f);
      mb0 = pack2(m0, m0);
      mb1 = pack2(m1, m1);
      center(0);
      TSC(3);
      stW(dA, 0, 0, -1);
      center(1);
      stW(dA, 1, 0, 0);
      const bool godd = lane & 4;
      const int src = (lane & ~3) | (lane >> 3);
      const float q0 = __shfl_sync(0xffffffffu, godd ? cq[0][1] + cq[2][1] : cq[0][0] + cq[2][0], src) * (1.f / 576.f);
      const float q1 = __shfl_sync(0xffffffffu, godd ? cq[1][3] + cq[3][3] : cq[1][2] + cq[3][2], src) * (1.f / 576.f);
      float v0 = q0 - m0 * m0, v1 = q1 - m1 * m1;
      if (__any_sync(0xffffffffu, v0 < q0 * (1.f / 64.f) || v1 < q1 * (1.f / 64.f))) {
        float s0 = 0.f, s1 = 0.f;
#pragma unroll 1
        for (int ks = 0; ks < 36; ks++) {
          uint32_t e0, e1, e2, e3;
          ldsm4(e0, e1, e2, e3, xa + (ks >> 2) * 16384 + (((2 * (ks & 3) + hi) ^ sw) << 4));
          float t;
          t = blo(e0) - m0; s0 = fmaf(t, t, s0); t = bhi(e0) - m0; s0 = fmaf(t, t, s0);
          t = blo(e2) - m0; s0 = fmaf(t, t, s0); t = bhi(e2) - m0; s0 = fmaf(t, t, s0);
          t = blo(e1) - m1; s1 = fmaf(t, t, s1); t = bhi(e1) - m1; s1 = fmaf(t, t, s1);
          t = blo(e3) - m1; s1 = fmaf(t, t, s1); t = bhi(e3) - m1; s1 = fmaf(t, t, s1);
        }
        s0 += __shfl_xor_sync(0xffffffffu, s0, 1); s1 += __shfl_xor_sync(0xffffffffu, s1, 1);
        s0 += __shfl_xor_sync(0xffffffffu, s0, 2); s1 += __shfl_xor_sync(0xffffffffu, s1, 2);
        v0 = s0 * (1.f / 576.f); v1 = s1 * (1.f / 576.f);
      }
      __syncwarp();
      if (l0) mbar_arrive(sb + B_XDONE);
      r0 = rcp(rbf(sqrta(rbf(rbf(fmaxf(v0, 0.f)) + 1e-5f))));
      r1 = rcp(rbf(sqrta(rbf(rbf(fmaxf(v1, 0.f)) + 1e-5f))));
    }
#pragma unroll
    for (int s = 2; s < 6; s++) {
      center(s);
      stW(dA, s, 0, s - 1);
    }
    TSC(4); GT(1);
    constexpr float LOG2E = 1.4426950408889634f;
    float l0e = r0 * LOG2E, l1e = r1 * LOG2E;
    const uint32_t tile_off = ((lane >> 4) + (j & 1)) * 2048 + (warp * 16 + (lane & 15)) * 16;
    mbar_wait(sb + B_XDONE, 0);
#pragma unroll
    for (int s = 0; s < 6; s++) {
      stW(dB, s, 1, (s + 5) % 6);
      if (s < 4) {
        const int t = 2 * s;
        pin8(dA, 4 * t);
        stsm4(sb + PK_T + tile_off + t * 2048, pack2(phi(dA[4 * t], r0, l0e), phi(dA[4 * t + 1], r0, l0e)), pack2(phi(dA[4 * t + 2], r1, l1e), phi(dA[4 * t + 3], r1, l1e)),
              pack2(phi(dA[4 * t + 4], r0, l0e), phi(dA[4 * t + 5], r0, l0e)), pack2(phi(dA[4 * t + 6], r1, l1e), phi(dA[4 * t + 7], r1, l1e)));
      }
    }
    TSC(5);
    {
#pragma unroll
      for (int s = 0; s < 2; s++) {
        stF(dA, s, 0, (s + 5) % 6);
#pragma unroll
        for (int t = 4 * s; t < 4 * s + 4; t += 2) {
          pin8(dB, 4 * t);
          stsm4(sb + V_T + tile_off + t * 2048, pack2(dB[4 * t] * r0, dB[4 * t + 1] * r0), pack2(dB[4 * t + 2] * r1, dB[4 * t + 3] * r1),
                pack2(dB[4 * t + 4] * r0, dB[4 * t + 5] * r0), pack2(dB[4 * t + 6] * r1, dB[4 * t + 7] * r1));
        }
      }
      float dL[12];
      constexpr uint64_t dl = mkdesc(sb + L24_T, 128, 576 * 16, 0);
      mbar_wait(sb + B_LFULL, 0);
#pragma unroll
      for (int s = 2; s < 5; s++) {
        mbar_wait(sb + B_FULL + 8 * s, 0);
        wg_fence();
#pragma unroll
        for (int ks = 12 * (s - 2); ks < 12 * (s - 1); ks++) wgmma_rs24(dL, a[ks], dl + ks * 16, ks != 0);
#pragma unroll
        for (int ks = 0; ks < 6; ks++) wgmma_rs64(dA, a[s * 6 + ks], dsw64 + ((s * SLOT + ks * 1024) >> 4), 1);
        finish(s - 1);
      }
      stF(dA, 5, 0, 4);
      pin(dL);
      const uint32_t lo = ((j & 1) ? 0 : 8 * 2048) + warp * 256 + lane * 4;
      sts32(sb + PK_T + lo, pack2(phi(dL[0], r0, l0e), phi(dL[1], r0, l0e)));
      sts32(sb + PK_T + lo + 128, pack2(phi(dL[2], r1, l1e), phi(dL[3], r1, l1e)));
      sts32(sb + V_T + lo, pack2(dL[4] * r0, dL[5] * r0));
      sts32(sb + V_T + lo + 128, pack2(dL[6] * r1, dL[7] * r1));
      sts64(sb + Q8 + tid * 8, pack2(dL[8], dL[9]), pack2(dL[10], dL[11]));
      fence_async_smem();
      __syncwarp();
      if (l0) mbar_arrive(sb + B_KVT);
    }
    TSC(6);
    uint32_t hs = sb + HB + wg * HHALF + (tid & 127) * 16;
    uint32_t hp0, hp1;
    const float iq0 = rcp(r0 * r0), iq1 = rcp(r1 * r1);
    auto epiF = [&](float (&d)[32], const int pc) {
      asm volatile("" : "+f"(d[4 * pc]), "+f"(d[4 * pc + 1]), "+f"(d[4 * pc + 2]), "+f"(d[4 * pc + 3]), "+f"(d[4 * pc + 16]), "+f"(d[4 * pc + 17]),
                   "+f"(d[4 * pc + 18]), "+f"(d[4 * pc + 19])::"memory");
      const float g0 = d[4 * pc], g1 = d[4 * pc + 1], g2 = d[4 * pc + 2], g3 = d[4 * pc + 3];
      const uint32_t h0 = pack2(g0 * d[4 * pc + 16] * rcp(fmaf(ex2(-g0 * l0e), iq0, iq0)), g1 * d[4 * pc + 17] * rcp(fmaf(ex2(-g1 * l0e), iq0, iq0)));
      const uint32_t h1 = pack2(g2 * d[4 * pc + 18] * rcp(fmaf(ex2(-g2 * l1e), iq1, iq1)), g3 * d[4 * pc + 19] * rcp(fmaf(ex2(-g3 * l1e), iq1, iq1)));
      if (pc & 1) {
        sts128(hs, hp0, hp1, h0, h1);
        hs += 2048;
      } else {
        hp0 = h0; hp1 = h1;
        asm volatile("" : "+r"(hp0), "+r"(hp1)::"memory");
      }
    };
    {
      stF(dB, 0, 1, 5);
      epiF(dA, 0); epiF(dA, 1);
      stF(dB, 1, 1, 0);
      epiF(dA, 2); epiF(dA, 3);
      float dK[20];
      const uint64_t ka = mkdesc(sb + V_T - 2048 + wg * 3 * 2048, 128, 2048, 0), kb = mkdesc(sb + PK_T + wg * 4 * 2048, 128, 2048, 0);
      mbar_wait(sb + B_KVT, 0);
      mbar_wait(sb + B_FULL + 8 * 2, 1);
      wg_fence();
#pragma unroll
      for (int ks = 0; ks < 8; ks++) wgmma_ss40tt(dK, ka + ks * 16, kb + ks * 16, ks != 0);
#pragma unroll
      for (int ks = 0; ks < 6; ks++) wgmma_rs64(dB, a[12 + ks], dsw64 + ((2 * SLOT + ks * 1024) >> 4), 1);
      finish(1);
      stF(dB, 3, 1, 2);
      pin(dK);
      float4* dst = g_kvp + (j * 16 + r) * 1280 + warp * 160 + lane;
#pragma unroll
      for (int t = 0; t < 5; t++) __stcg(dst + t * 32, make_float4(dK[4 * t], dK[4 * t + 1], dK[4 * t + 2], dK[4 * t + 3]));
      __syncwarp();
      if (l0) mbar_arrive(sb + B_KVD);
      stF(dB, 4, 1, 3);
    }
#pragma unroll 1
    for (int it = 0; it < 8; it++) {
      stF(dB, 5, 1, 4);
      stF(dA, 0, 0, 5);
#pragma unroll
      for (int s = 1; s < 5; s++) { epiF(dB, s - 1); stF(dA, s, 0, s - 1); }
      stF(dA, 5, 0, 4);
      stF(dB, 0, 1, 5);
#pragma unroll
      for (int s = 1; s < 5; s++) { epiF(dA, s - 1); stF(dB, s, 1, s - 1); }
      TSC(7 + it);
    }
    stF(dB, 5, 1, 4);
    TSC(15);
    const uint32_t hl = sb + HB + wg * HHALF + (tid & 127) * 16;
    auto reload = [&](auto k0, auto k1) {
      static_for<decltype(k0)::value, decltype(k1)::value>([&](auto k) { lds128_inplace<decltype(k)::value * 2048>(a[decltype(k)::value], hl); });
    };
    stW(dA, 0, 0, 5);
    epiF(dB, 0);
    stW(dA, 1, 0, 0);
    reload(IC<0>(), IC<4>());
    epiF(dB, 1);
    stW(dA, 2, 0, 1);
    reload(IC<4>(), IC<8>());
    epiF(dB, 2);
    stW(dA, 3, 0, 2);
    reload(IC<8>(), IC<12>());
    __syncwarp();
    if (l0 && wg == 0) mbar_arrive(sb + B_HFREE);
    epiF(dB, 3);
    stW(dA, 4, 0, 3);
    reload(IC<12>(), IC<17>());
    stW(dA, 5, 0, 4);
    reload(IC<17>(), IC<22>());
    const uint32_t ot = sb + HB + wg * HHALF;
    const uint32_t do_a = (uint32_t)mkdesc(ot, 128, 1280, 0);
    constexpr uint64_t do_b = mkdesc(sb + WO_SLOT, 16, 1024, 1);
    auto stO = [&](float (&d)[32], const uint32_t ph, const int rel) {
      mbar_wait(sb + B_FULL + 48, ph);
      wg_fence();
      wgmma_ss64<0, 80>(d, do_a, do_b);
      wgmma_ss64<16, 80>(d, do_a, do_b + 128);
      wgmma_ss64<32, 80>(d, do_a, do_b + 256);
      wgmma_ss64<48, 80>(d, do_a, do_b + 384);
      wgmma_ss64<64, 80>(d, do_a, do_b + 512);
      finish(rel);
    };
    uint32_t tag;
    auto epiP = [&](float (&d)[32], const int step) {
      pin(d);
      const int c = step == 0 ? 8 : ((j + step) & 7);
      uint4* dst = g_part + (size_t)((r * 9 + c) * 8 + j) * 1024 + warp * 128 + lane;
#pragma unroll
      for (int i = 0; i < 4; i++)
        st_b128(dst + i * 32, (pack2(d[8 * i], d[8 * i + 1]) & 0xfffeffffu) | tag, pack2(d[8 * i + 2], d[8 * i + 3]), pack2(d[8 * i + 4], d[8 * i + 5]), pack2(d[8 * i + 6], d[8 * i + 7]));
    };
    TSC(16);
    {
      stW(dB, 0, 1, 5);
      reload(IC<22>(), IC<26>());
      asm volatile("" : "+f"(l0e), "+f"(l1e));
      r0 = l0e * (1.f / LOG2E); r1 = l1e * (1.f / LOG2E);
      uint32_t pq[18];
      const uint32_t oa = ot + ((warp & 3) * 2 + ((lane >> 3) & 1)) * 1280 + (lane >> 4) * 128 + (lane & 7) * 16;
      auto phiq = [&](const int t0, const int t1) {
#pragma unroll
        for (int t = t0; t < t1; t++) {
          asm volatile("" : "+f"(dA[4 * t]), "+f"(dA[4 * t + 1]), "+f"(dA[4 * t + 2]), "+f"(dA[4 * t + 3])::"memory");
          pq[2 * t] = pack2(phi(dA[4 * t], r0, l0e), phi(dA[4 * t + 1], r0, l0e));
          pq[2 * t + 1] = pack2(phi(dA[4 * t + 2], r1, l1e), phi(dA[4 * t + 3], r1, l1e));
          asm volatile("" : "+r"(pq[2 * t]), "+r"(pq[2 * t + 1])::"memory");
        }
      };
      phiq(0, 3);
      bar_sync(1 + wg, 128);
      stW(dB, 1, 1, 0);
      reload(IC<26>(), IC<30>());
      phiq(3, 6);
      stW(dB, 2, 1, 1);
      phiq(6, 8);
      {
        uint32_t q0, q1;
        lds64(q0, q1, sb + Q8 + tid * 8);
        pq[16] = pack2(phi(blo(q0), r0, l0e), phi(bhi(q0), r0, l0e));
        pq[17] = pack2(phi(blo(q1), r1, l1e), phi(bhi(q1), r1, l1e));
      }
#pragma unroll
      for (int t = 0; t < 8; t += 2) stsm4(oa + t * 128, pq[2 * t], pq[2 * t + 1], pq[2 * t + 2], pq[2 * t + 3]);
      stsm4(oa + 1024, pq[16], pq[17], 0u, 0u);
      fence_async_smem();
      TSC(17);
      mbar_wait(sb + B_MRDY, 0);
      TSC(18);
      tag = lds32(sb + TAGW);
      float den[8];
      constexpr uint64_t dz = mkdesc(sb + ZM, 128, 1280, 0);
      bar_sync(1 + wg, 128);
      issue(dB, dsw128, 2048, 3, 1);
      wgmma_ss16<0, 80, 0>(den, do_a, dz);
      wgmma_ss16<16, 80, 1>(den, do_a, dz + 16);
      wgmma_ss16<32, 80, 1>(den, do_a, dz + 32);
      wgmma_ss16<48, 80, 1>(den, do_a, dz + 48);
      wgmma_ss16<64, 80, 1>(den, do_a, dz + 64);
      finish(2);
      reload(IC<30>(), IC<36>());
      stW(dB, 4, 1, 3);
      pin(den);
      uint32_t iv[8];
#pragma unroll
      for (int i = 0; i < 8; i++) { const float t = rcp(den[i] + 1e-6f); iv[i] = pack2(t, t); }
      const int u = 2 * (lane & 3) + 8 * (j & 1);
#pragma unroll
      for (int t = 0; t < 10; t += 2) {
        uint32_t o[4];
#pragma unroll
        for (int z = 0; z < 2; z++) {
          const int tt = t + z;
          if (tt < 9) {
            const int lo = tt == 0 ? 0 : tt >= 7 ? 3 : (tt - 1) >> 1, hi = tt == 8 ? 0 : (tt == 0 || tt == 7) ? lo : lo + 1;
            const bool up = tt == 8 ? (j & 1) : 8 * tt + u >= 18 * hi;
            const int il = (lo >> 1) * 4 + (lo & 1), ih = (hi >> 1) * 4 + (hi & 1);
            o[2 * z] = bmul2(pq[2 * tt], up ? iv[ih] : iv[il]);
            o[2 * z + 1] = bmul2(pq[2 * tt + 1], up ? iv[ih + 2] : iv[il + 2]);
          } else {
            o[2 * z] = 0; o[2 * z + 1] = 0;
          }
        }
        stsm4(oa + t * 128, o[0], o[1], o[2], o[3]);
      }
      fence_async_smem();
      stW(dB, 5, 1, 4);
      bar_sync(1 + wg, 128);
      stO(dB, 0, 5);
    }
    stW(dA, 0, 0, 6);
    epiP(dB, 0);
    TSC(19);
    auto ldp = [&](uint32_t (&v)[16], const int c, const int dj) {
      const uint4* src = g_part + (size_t)((r * 9 + c) * 8 + ((j + dj) & 7)) * 1024 + warp * 128 + lane;
#pragma unroll
      for (int i = 0; i < 4; i++) ld_b128(v[4 * i], v[4 * i + 1], v[4 * i + 2], v[4 * i + 3], src + i * 32);
    };
    auto chk = [&](uint32_t (&v)[16], const int c, const int dj) {
      uint32_t n = 0;
      while (__any_sync(0xffffffffu, (((v[0] ^ tag) | (v[4] ^ tag) | (v[8] ^ tag) | (v[12] ^ tag)) & 0x10000u) != 0)) {
        ldp(v, c, dj);
        if (++n > SPIN_LIMIT) asm volatile("trap;");
      }
    };
    auto unp = [&](float (&d)[32], uint32_t (&v)[16], const int i) {
      d[8 * i] = blo(v[4 * i]); d[8 * i + 1] = __uint_as_float(v[4 * i] & 0xfffe0000u); d[8 * i + 2] = blo(v[4 * i + 1]); d[8 * i + 3] = bhi(v[4 * i + 1]);
      d[8 * i + 4] = blo(v[4 * i + 2]); d[8 * i + 5] = bhi(v[4 * i + 2]); d[8 * i + 6] = blo(v[4 * i + 3]); d[8 * i + 7] = bhi(v[4 * i + 3]);
      pin8(d, 8 * i);
    };
#pragma unroll
    for (int s = 1; s < 6; s++) stW(dA, s, 0, s - 1);
    stO(dA, 1, 5);
    stW(dB, 0, 1, 6);
    epiP(dA, 1);
    TSC(20);
#pragma unroll 1
    for (int it = 0; it < 3; it++) {
      uint32_t v[16];
      stW(dB, 1, 1, 0);
#pragma unroll
      for (int i = 0; i < 16; i++) v[i] = (i & 3) ? 0u : tag;
      if (it > 0) ldp(v, (j + 3 + 2 * it) & 7, 3);
      stW(dB, 2, 1, 1);
      stW(dB, 3, 1, 2);
      stW(dB, 4, 1, 3);
      chk(v, (j + 3 + 2 * it) & 7, 3);
      unp(dA, v, 0); unp(dA, v, 1);
      stW(dB, 5, 1, 4);
      unp(dA, v, 2); unp(dA, v, 3);
      stO(dB, 0, 5);
      issue(dA, dsw128, 2048, 0, 0, 1); finish(6);
      epiP(dB, 2 + 2 * it);
      stW(dA, 1, 0, 0);
      ldp(v, (j + 4 + 2 * it) & 7, 3);
      stW(dA, 2, 0, 1);
      stW(dA, 3, 0, 2);
      stW(dA, 4, 0, 3);
      chk(v, (j + 4 + 2 * it) & 7, 3);
      unp(dB, v, 0); unp(dB, v, 1);
      stW(dA, 5, 0, 4);
      unp(dB, v, 2); unp(dB, v, 3);
      stO(dA, 1, 5);
      issue(dB, dsw128, 2048, 0, 1, 1); finish(6);
      epiP(dA, 3 + 2 * it);
      TSC(21 + it);
    }
    {
      uint32_t v[16], w[16], xv[16];
      float f[32];
      auto addv = [&](uint32_t (&v)[16], const int i) {
        f[8 * i] += blo(v[4 * i]); f[8 * i + 1] += __uint_as_float(v[4 * i] & 0xfffe0000u); f[8 * i + 2] += blo(v[4 * i + 1]); f[8 * i + 3] += bhi(v[4 * i + 1]);
        f[8 * i + 4] += blo(v[4 * i + 2]); f[8 * i + 5] += bhi(v[4 * i + 2]); f[8 * i + 6] += blo(v[4 * i + 3]); f[8 * i + 7] += bhi(v[4 * i + 3]);
        pin8(f, 8 * i);
      };
      const uint32_t* xp = reinterpret_cast<const uint32_t*>(p.x + (size_t)(r * 128 + warp * 16 + (lane >> 2)) * D_ + 64 * j + 2 * (lane & 3));
      stW(dB, 1, 1, -1);
      ldp(v, j, 2);
#pragma unroll
      for (int t = 0; t < 8; t++) { xv[2 * t] = __ldg(xp + 4 * t); xv[2 * t + 1] = __ldg(xp + 4 * D_ + 4 * t); }
      stW(dB, 2, 1, -1);
      stW(dB, 3, 1, -1);
      ldp(w, j, 1);
      stW(dB, 4, 1, -1);
#pragma unroll
      for (int i = 0; i < 16; i++) { f[2 * i] = blo(xv[i]); f[2 * i + 1] = bhi(xv[i]); }
      chk(v, j, 2);
      addv(v, 0);
      stW(dB, 5, 1, -1);
      addv(v, 1); addv(v, 2); addv(v, 3);
      stO(dB, 0, -1);
      TSC(24);
      chk(w, j, 1);
      addv(w, 0); addv(w, 1); addv(w, 2); addv(w, 3);
      TSC(25);
      wg_wait<0>();
      TSC(26); GT(2);
      pin(dB);
      const uint32_t ps = sb + HB + wg * HHALF + STG + (warp & 3) * 2048;
      const int row = lane & 15;
#pragma unroll
      for (int t = 0; t < 8; t += 2)
        stsm4(ps + row * 128 + (((t + (lane >> 4)) ^ (row & 7)) << 4),
              pack2(f[4 * t] + dB[4 * t], f[4 * t + 1] + dB[4 * t + 1]), pack2(f[4 * t + 2] + dB[4 * t + 2], f[4 * t + 3] + dB[4 * t + 3]),
              pack2(f[4 * t + 4] + dB[4 * t + 4], f[4 * t + 5] + dB[4 * t + 5]), pack2(f[4 * t + 6] + dB[4 * t + 6], f[4 * t + 7] + dB[4 * t + 7]));
      __syncwarp();
#pragma unroll
      for (int i = 0; i < 4; i++) {
        const int rr = i * 4 + (lane >> 3), ch = lane & 7;
        uint4 o;
        lds128(o.x, o.y, o.z, o.w, ps + rr * 128 + ((ch ^ (rr & 7)) << 4));
        *reinterpret_cast<uint4*>(p.out + (size_t)(r * 128 + warp * 16 + rr) * D_ + 64 * j + ch * 8) = o;
      }
    }
    TSC(27); GT(3);
  }
}

typedef CUresult (*EncodeFn)(CUtensorMap*, CUtensorMapDataType, cuuint32_t, void*, const cuuint64_t*, const cuuint64_t*, const cuuint32_t*,
                             const cuuint32_t*, CUtensorMapInterleave, CUtensorMapSwizzle, CUtensorMapL2promotion, CUtensorMapFloatOOBfill);

CUtensorMap make_map(EncodeFn enc, const void* ptr, int rows, int cols, int brow, int bcol, CUtensorMapSwizzle sw) {
  CUtensorMap m;
  cuuint64_t gd[2] = {(cuuint64_t)cols, (cuuint64_t)rows};
  cuuint64_t gs[1] = {(cuuint64_t)cols * 2};
  cuuint32_t bd[2] = {(cuuint32_t)bcol, (cuuint32_t)brow};
  cuuint32_t es[2] = {1, 1};
  enc(&m, CU_TENSOR_MAP_DATA_TYPE_BFLOAT16, 2, const_cast<void*>(ptr), gd, gs, bd, es, CU_TENSOR_MAP_INTERLEAVE_NONE, sw,
      CU_TENSOR_MAP_L2_PROMOTION_L2_128B, CU_TENSOR_MAP_FLOAT_OOB_FILL_NONE);
  return m;
}

}

extern "C" void kernel_launch(void* const* d_in, const int* in_sizes, int n_in, void* d_out, int out_size) {
  (void)in_sizes; (void)n_in; (void)out_size;
  static EncodeFn enc = nullptr;
  static void* m_ptr = nullptr;
  if (!enc) {
    cudaGetSymbolAddress(&m_ptr, g_M);
    cudaDriverEntryPointQueryResult qr;
    cudaGetDriverEntryPoint("cuTensorMapEncodeTiled", (void**)&enc, cudaEnableDefault, &qr);
    cudaFuncSetAttribute(fused_block_kernel, cudaFuncAttributeMaxDynamicSharedMemorySize, SMEM_BYTES);
  }
  Params p;
  p.x = (const __nv_bfloat16*)d_in[0];
  p.wqkv = (const __nv_bfloat16*)d_in[1];
  p.wo = (const __nv_bfloat16*)d_in[2];
  p.w1 = (const __nv_bfloat16*)d_in[4];
  p.w3 = (const __nv_bfloat16*)d_in[5];
  p.w2 = (const __nv_bfloat16*)d_in[6];
  p.out = (__nv_bfloat16*)d_out;
  const CUtensorMap m_qkv = make_map(enc, p.wqkv, D_, 3 * D_, 96, 64, CU_TENSOR_MAP_SWIZZLE_128B);
  const CUtensorMap m_w1 = make_map(enc, p.w1, D_, F_, 96, 32, CU_TENSOR_MAP_SWIZZLE_64B);
  const CUtensorMap m_w3 = make_map(enc, p.w3, D_, F_, 96, 32, CU_TENSOR_MAP_SWIZZLE_64B);
  const CUtensorMap m_w2 = make_map(enc, p.w2, F_, D_, 96, 64, CU_TENSOR_MAP_SWIZZLE_128B);
  const CUtensorMap m_M = make_map(enc, m_ptr, 8 * 80, D_, 80, 64, CU_TENSOR_MAP_SWIZZLE_128B);
  const CUtensorMap m_x = make_map(enc, p.x, 2048, D_, 128, 64, CU_TENSOR_MAP_SWIZZLE_128B);
  fused_block_kernel<<<128, NTHREADS, SMEM_BYTES>>>(m_qkv, m_w1, m_w3, m_w2, m_M, m_x, p);
}
```

```cpp
#include <cuda_runtime.h>
#include <cuda.h>
#include <cuda_bf16.h>
#include <stdint.h>

namespace {

constexpr int D_ = 576, F_ = 4608;
constexpr int NTHREADS = 384;

constexpr uint32_t SLOT = 12288;
constexpr uint32_t HB = 6 * SLOT;
constexpr uint32_t HHALF = 73728;
constexpr uint32_t PK_T = HB + 45056;
constexpr uint32_t V_T = HB + HHALF + 18432;
constexpr uint32_t L24_T = HB + 16384;
constexpr uint32_t WO_SLOT = HB + 12288;
constexpr uint32_t XT = HB + 24576;
constexpr uint32_t STG = 49152;
constexpr uint32_t Q8 = HB + 2 * HHALF;
constexpr uint32_t WOB = Q8 + 2048;
constexpr uint32_t KVS = WOB + 5184;
constexpr uint32_t ZM = WOB;
constexpr uint32_t TAGW = KVS + 1440;
constexpr uint32_t BARS = TAGW + 32;
constexpr uint32_t SMEM_BYTES = BARS + 512;

constexpr uint32_t B_X = BARS;
constexpr uint32_t B_FULL = BARS + 8 * 9;
constexpr uint32_t B_EMPTY = BARS + 8 * 16;
constexpr uint32_t B_XDONE = BARS + 8 * 23;
constexpr uint32_t B_KVT = BARS + 8 * 24;
constexpr uint32_t B_KVD = BARS + 8 * 25;
constexpr uint32_t B_HFREE = BARS + 8 * 26;
constexpr uint32_t B_LFULL = BARS + 8 * 27;
constexpr uint32_t B_MRDY = BARS + 8 * 28;

#define XPF 4
#define WDELAY 2
#define XWAIT 8
constexpr uint32_t SPIN_LIMIT = 1u << 22;

__device__ uint4 g_part[16 * 9 * 8 * 1024];
__device__ float4 g_kvp[8 * 16 * 1280];
__device__ __align__(128) __nv_bfloat16 g_M[8 * 80 * 576];
__device__ __align__(16) float g_z[8 * 72];
__device__ uint32_t g_cnt1[8 * 32], g_cnt2[8 * 32];
__device__ uint32_t g_epoch[128];

#define TS(slot, i)
#define TSC(i)
#define GT(i)

__device__ __forceinline__ void wg_fence() { asm volatile("wgmma.fence.sync.aligned;\n" ::: "memory"); }
__device__ __forceinline__ void wg_commit() { asm volatile("wgmma.commit_group.sync.aligned;\n" ::: "memory"); }
template <int N> __device__ __forceinline__ void wg_wait() { asm volatile("wgmma.wait_group.sync.aligned %0;\n" ::"n"(N) : "memory"); }
__host__ __device__ constexpr uint64_t mkdesc(uint32_t addr, uint32_t lbo, uint32_t sbo, uint32_t sw) {
  return (uint64_t)((addr & 0x3FFFF) >> 4) | ((uint64_t)(lbo >> 4) << 16) | ((uint64_t)(sbo >> 4) << 32) | ((uint64_t)sw << 62);
}
__device__ __forceinline__ void mbar_init(uint32_t a, uint32_t c) { asm volatile("mbarrier.init.shared::cta.b64 [%0], %1;\n" ::"r"(a), "r"(c) : "memory"); }
__device__ __forceinline__ void mbar_expect(uint32_t a, uint32_t b) { asm volatile("mbarrier.arrive.expect_tx.shared::cta.b64 _, [%0], %1;\n" ::"r"(a), "r"(b) : "memory"); }
__device__ __forceinline__ void mbar_arrive(uint32_t a) { asm volatile("mbarrier.arrive.shared::cta.b64 _, [%0];\n" ::"r"(a) : "memory"); }
__device__ __forceinline__ void mbar_wait(uint32_t a, uint32_t ph) {
  asm volatile(
      "{\n.reg .pred p;\n.reg .u32 n;\n"
      "mov.u32 n, 0;\n"
      "LOOP:\n"
      "mbarrier.try_wait.parity.shared::cta.b64 p, [%0], %1;\n"
      "@p bra DONE;\n"
      "add.u32 n, n, 1;\n"
      "setp.gt.u32 p, n, %2;\n"
      "@p trap;\n"
      "bra LOOP;\n"
      "DONE:\n}\n" ::"r"(a), "r"(ph), "n"(SPIN_LIMIT) : "memory");
}
__device__ __forceinline__ void cp_async16(uint32_t dst, const void* src) {
  asm volatile("cp.async.cg.shared.global [%0], [%1], 16;\n" ::"r"(dst), "l"(src) : "memory");
}
__device__ __forceinline__ void tma2d(uint32_t dst, const CUtensorMap* m, int c0, int c1, uint32_t bar) {
  asm volatile("cp.async.bulk.tensor.2d.shared::cluster.global.mbarrier::complete_tx::bytes [%0], [%1, {%3, %4}], [%2];\n" ::"r"(dst), "l"(m), "r"(bar), "r"(c0), "r"(c1) : "memory");
}
__device__ __forceinline__ void tma2d_prefetch(const CUtensorMap* m, int c0, int c1) {
  asm volatile("cp.async.bulk.prefetch.tensor.2d.L2.global [%0, {%1, %2}];\n" ::"l"(m), "r"(c0), "r"(c1) : "memory");
}
__device__ __forceinline__ void fence_async_smem() { asm volatile("fence.proxy.async.shared::cta;\n" ::: "memory"); }
__device__ __forceinline__ void bar_sync(int id, int n) { asm volatile("bar.sync %0, %1;\n" ::"r"(id), "r"(n) : "memory"); }
__device__ __forceinline__ void ldsm4(uint32_t& r0, uint32_t& r1, uint32_t& r2, uint32_t& r3, uint32_t a) {
  asm volatile("ldmatrix.sync.aligned.m8n8.x4.shared.b16 {%0,%1,%2,%3}, [%4];\n" : "=r"(r0), "=r"(r1), "=r"(r2), "=r"(r3) : "r"(a) : "memory");
}
__device__ __forceinline__ void stsm4(uint32_t a, uint32_t r0, uint32_t r1, uint32_t r2, uint32_t r3) {
  asm volatile("stmatrix.sync.aligned.m8n8.x4.shared.b16 [%0], {%1,%2,%3,%4};\n" ::"r"(a), "r"(r0), "r"(r1), "r"(r2), "r"(r3) : "memory");
}
__device__ __forceinline__ void sts128(uint32_t a, uint32_t r0, uint32_t r1, uint32_t r2, uint32_t r3) {
  asm volatile("st.shared.v4.b32 [%0], {%1,%2,%3,%4};\n" ::"r"(a), "r"(r0), "r"(r1), "r"(r2), "r"(r3) : "memory");
}
__device__ __forceinline__ void lds128(uint32_t& r0, uint32_t& r1, uint32_t& r2, uint32_t& r3, uint32_t a) {
  asm volatile("ld.shared.v4.b32 {%0,%1,%2,%3}, [%4];\n" : "=r"(r0), "=r"(r1), "=r"(r2), "=r"(r3) : "r"(a) : "memory");
}
template <int OFF>
__device__ __forceinline__ void lds128_inplace(uint32_t (&r)[4], uint32_t a) {
  asm volatile("{\n.reg .pred p;\nsetp.ne.u32 p, %4, 0;\n@p ld.shared.v4.b32 {%0,%1,%2,%3}, [%4 + %5];\n}\n"
               : "+r"(r[0]), "+r"(r[1]), "+r"(r[2]), "+r"(r[3]) : "r"(a), "n"(OFF) : "memory");
}
__device__ __forceinline__ void sts64(uint32_t a, uint32_t r0, uint32_t r1) { asm volatile("st.shared.v2.b32 [%0], {%1,%2};\n" ::"r"(a), "r"(r0), "r"(r1) : "memory"); }
__device__ __forceinline__ void lds64(uint32_t& r0, uint32_t& r1, uint32_t a) { asm volatile("ld.shared.v2.b32 {%0,%1}, [%2];\n" : "=r"(r0), "=r"(r1) : "r"(a) : "memory"); }
__device__ __forceinline__ uint32_t lds32(uint32_t a) { uint32_t v; asm volatile("ld.shared.b32 %0, [%1];\n" : "=r"(v) : "r"(a) : "memory"); return v; }
__device__ __forceinline__ void sts32(uint32_t a, uint32_t r0) { asm volatile("st.shared.b32 [%0], %1;\n" ::"r"(a), "r"(r0) : "memory"); }
__device__ __forceinline__ void mma16816(float (&c)[4], uint32_t a0, uint32_t a1, uint32_t a2, uint32_t a3, uint32_t b0, uint32_t b1) {
  asm volatile("mma.sync.aligned.m16n8k16.row.col.f32.bf16.bf16.f32 {%0,%1,%2,%3}, {%4,%5,%6,%7}, {%8,%9}, {%0,%1,%2,%3};\n"
               : "+f"(c[0]), "+f"(c[1]), "+f"(c[2]), "+f"(c[3]) : "r"(a0), "r"(a1), "r"(a2), "r"(a3), "r"(b0), "r"(b1));
}
__device__ __forceinline__ void mma1688(float (&c)[4], uint32_t a0, uint32_t a1, uint32_t b0) {
  asm volatile("mma.sync.aligned.m16n8k8.row.col.f32.bf16.bf16.f32 {%0,%1,%2,%3}, {%4,%5}, {%6}, {%0,%1,%2,%3};\n"
               : "+f"(c[0]), "+f"(c[1]), "+f"(c[2]), "+f"(c[3]) : "r"(a0), "r"(a1), "r"(b0));
}
__device__ __forceinline__ uint32_t pack2(float lo, float hi) {
  uint32_t r;
  asm("cvt.rn.bf16x2.f32 %0, %1, %2;\n" : "=r"(r) : "f"(hi), "f"(lo));
  return r;
}
__device__ __forceinline__ float blo(uint32_t w) { return __uint_as_float(w << 16); }
__device__ __forceinline__ float bhi(uint32_t w) { return __uint_as_float(w & 0xffff0000u); }
__device__ __forceinline__ float rbf(float x) { return __bfloat162float(__float2bfloat16_rn(x)); }
__device__ __forceinline__ float ex2(float x) { float r; asm("ex2.approx.ftz.f32 %0, %1;\n" : "=f"(r) : "f"(x)); return r; }
__device__ __forceinline__ float rcp(float x) { float r; asm("rcp.approx.ftz.f32 %0, %1;\n" : "=f"(r) : "f"(x)); return r; }
__device__ __forceinline__ float sqrta(float x) { float r; asm("sqrt.approx.ftz.f32 %0, %1;\n" : "=f"(r) : "f"(x)); return r; }
__device__ __forceinline__ uint32_t bsub2(uint32_t a, uint32_t b) { uint32_t r; asm("sub.rn.bf16x2 %0, %1, %2;\n" : "=r"(r) : "r"(a), "r"(b)); return r; }
__device__ __forceinline__ uint32_t ld_acq(const uint32_t* p) { uint32_t v; asm volatile("ld.acquire.gpu.global.u32 %0, [%1];\n" : "=r"(v) : "l"(p) : "memory"); return v; }
__device__ __forceinline__ void st_b128(void* p, uint32_t a, uint32_t b, uint32_t c, uint32_t d) {
  asm volatile("st.relaxed.gpu.global.v4.b32 [%0], {%1, %2, %3, %4};\n" ::"l"(p), "r"(a), "r"(b), "r"(c), "r"(d) : "memory");
}
__device__ __forceinline__ void ld_b128(uint32_t& a, uint32_t& b, uint32_t& c, uint32_t& d, const void* p) {
  asm volatile("{\n.reg .b128 v;\nld.relaxed.gpu.global.b128 v, [%4];\nmov.b128 {%0, %1, %2, %3}, v;\n}\n" : "=r"(a), "=r"(b), "=r"(c), "=r"(d) : "l"(p) : "memory");
}
__device__ __forceinline__ bool elect_one() {
  uint32_t ok;
  asm volatile("{\n.reg .pred p;\nelect.sync _|p, 0xffffffff;\nselp.u32 %0, 1, 0, p;\n}\n" : "=r"(ok));
  return ok;
}
__device__ __forceinline__ uint32_t bmul2(uint32_t a, uint32_t b) { uint32_t r; asm("mul.rn.bf16x2 %0, %1, %2;\n" : "=r"(r) : "r"(a), "r"(b)); return r; }
__device__ __forceinline__ void red_rel(uint32_t* p) { asm volatile("red.release.gpu.global.add.u32 [%0], 1;\n" ::"l"(p) : "memory"); }
__device__ __forceinline__ void wait_ge(const uint32_t* p, uint32_t target) {
  uint32_t n = 0;
  while ((int32_t)(ld_acq(p) - target) < 0) {
    __nanosleep(64);
    if (++n > SPIN_LIMIT) __trap();
  }
}
__device__ __forceinline__ float phi(float a, float r, float rl) { return fmaf(fmaxf(a, 0.f), r, __saturatef(ex2(a * rl) + 1e-6f)); }

#define ACC8(d, o) "+f"(d[o + 0]), "+f"(d[o + 1]), "+f"(d[o + 2]), "+f"(d[o + 3]), "+f"(d[o + 4]), "+f"(d[o + 5]), "+f"(d[o + 6]), "+f"(d[o + 7])
#define REGS32 "{%0,%1,%2,%3,%4,%5,%6,%7,%8,%9,%10,%11,%12,%13,%14,%15,%16,%17,%18,%19,%20,%21,%22,%23,%24,%25,%26,%27,%28,%29,%30,%31}"
__device__ __forceinline__ void wgmma_rs64(float (&d)[32], const uint32_t (&a)[4], uint64_t db, int acc) {
  asm volatile("{\n.reg .pred p;\nsetp.ne.b32 p, %37, 0;\n"
               "wgmma.mma_async.sync.aligned.m64n64k16.f32.bf16.bf16 " REGS32 ", {%32,%33,%34,%35}, %36, p, 1, 1, 1;\n}\n"
               : ACC8(d, 0), ACC8(d, 8), ACC8(d, 16), ACC8(d, 24)
               : "r"(a[0]), "r"(a[1]), "r"(a[2]), "r"(a[3]), "l"(db), "r"(acc));
}
template <uint32_t OFF, uint32_t HI>
__device__ __forceinline__ void wgmma_ss64(float (&d)[32], uint32_t da_lo, uint64_t db) {
  asm volatile("{\n.reg .b32 lo;\n.reg .b64 da;\nadd.u32 lo, %32, %34;\nmov.b64 da, {lo, %35};\n"
               "wgmma.mma_async.sync.aligned.m64n64k16.f32.bf16.bf16 " REGS32 ", da, %33, 1, 1, 1, 0, 1;\n}\n"
               : ACC8(d, 0), ACC8(d, 8), ACC8(d, 16), ACC8(d, 24)
               : "r"(da_lo), "l"(db), "n"(OFF), "n"(HI));
}
__device__ __forceinline__ void wgmma_rs24(float (&d)[12], const uint32_t (&a)[4], uint64_t db, int acc) {
  asm volatile("{\n.reg .pred p;\nsetp.ne.b32 p, %17, 0;\n"
               "wgmma.mma_async.sync.aligned.m64n24k16.f32.bf16.bf16 {%0,%1,%2,%3,%4,%5,%6,%7,%8,%9,%10,%11}, {%12,%13,%14,%15}, %16, p, 1, 1, 1;\n}\n"
               : ACC8(d, 0), "+f"(d[8]), "+f"(d[9]), "+f"(d[10]), "+f"(d[11])
               : "r"(a[0]), "r"(a[1]), "r"(a[2]), "r"(a[3]), "l"(db), "r"(acc));
}
__device__ __forceinline__ void wgmma_ss40tt(float (&d)[20], uint64_t da, uint64_t db, int acc) {
  asm volatile("{\n.reg .pred p;\nsetp.ne.b32 p, %22, 0;\n"
               "wgmma.mma_async.sync.aligned.m64n40k16.f32.bf16.bf16 {%0,%1,%2,%3,%4,%5,%6,%7,%8,%9,%10,%11,%12,%13,%14,%15,%16,%17,%18,%19}, %20, %21, p, 1, 1, 1, 1;\n}\n"
               : ACC8(d, 0), ACC8(d, 8), "+f"(d[16]), "+f"(d[17]), "+f"(d[18]), "+f"(d[19])
               : "l"(da), "l"(db), "r"(acc));
}
template <uint32_t OFF, uint32_t HI, int ACCUM>
__device__ __forceinline__ void wgmma_ss16(float (&d)[8], uint32_t da_lo, uint64_t db) {
  asm volatile("{\n.reg .b32 lo;\n.reg .b64 da;\n.reg .pred p;\nsetp.ne.b32 p, %12, 0;\nadd.u32 lo, %8, %10;\nmov.b64 da, {lo, %11};\n"
               "wgmma.mma_async.sync.aligned.m64n16k16.f32.bf16.bf16 {%0,%1,%2,%3,%4,%5,%6,%7}, da, %9, p, 1, 1, 0, 1;\n}\n"
               : ACC8(d, 0)
               : "r"(da_lo), "l"(db), "n"(OFF), "n"(HI), "n"(ACCUM));
}
template <int N> __device__ __forceinline__ void pin(float (&d)[N]) {
#pragma unroll
  for (int i = 0; i < N; i++) asm volatile("" : "+f"(d[i])::"memory");
}

__device__ __forceinline__ void pin8(float (&d)[32], const int o) { asm volatile("" : ACC8(d, o)::"memory"); }

template <int I> struct IC { static constexpr int value = I; };
template <int I, int N, class F> __device__ __forceinline__ void static_for(F f) {
  if constexpr (I < N) { f(IC<I>()); static_for<I + 1, N>(f); }
}

struct Params {
  const __nv_bfloat16* x;
  const __nv_bfloat16* wqkv;
  const __nv_bfloat16* wo;
  const __nv_bfloat16* w1;
  const __nv_bfloat16* w3;
  const __nv_bfloat16* w2;
  __nv_bfloat16* out;
};

__global__ void __launch_bounds__(NTHREADS, 1)
fused_block_kernel(const __grid_constant__ CUtensorMap m_qkv, const __grid_constant__ CUtensorMap m_w1,
                   const __grid_constant__ CUtensorMap m_w3, const __grid_constant__ CUtensorMap m_w2,
                   const __grid_constant__ CUtensorMap m_M, const __grid_constant__ CUtensorMap m_x, const Params p) {
  extern __shared__ __align__(1024) uint8_t smem_raw[];
  constexpr uint32_t sb = 1024;
  if ((uint32_t)__cvta_generic_to_shared(smem_raw) != sb) __trap();
  const int tid = threadIdx.x, warp = __shfl_sync(0xffffffffu, tid >> 5, 0), lane = tid & 31;
  const int r = blockIdx.x >> 3, j = blockIdx.x & 7;

  GT(0); TSC(0);
  if (tid < 16 * XPF) asm volatile("prefetch.global.L2 [%0];\n" ::"l"(p.x + (size_t)(blockIdx.x * 16 + (tid & 15)) * D_ + (tid >> 4) * 64));
  const int cmain = 72 * j + 8 * (j & 1);
  if (__builtin_expect(warp >= 8, 1)) {
    asm volatile("setmaxnreg.dec.sync.aligned.u32 24;\n");
    if (__builtin_expect(warp == 8, 1)) {
      if (elect_one()) {
#pragma unroll
        for (int b = 0; b < 9; b++) mbar_init(sb + B_X + 8 * b, 1);
        asm volatile("fence.mbarrier_init.release.cluster;\n" ::: "memory");
        mbar_expect(sb + B_X, 16384);
        tma2d(sb + HB, &m_x, 0, 128 * r, sb + B_X);
      }
      __syncwarp();
      asm volatile("bar.arrive 0, 384;\n" ::: "memory");
      TS(2, 20);
      if (elect_one()) {
#pragma unroll
        for (int b = 1; b < 9; b++) {
          mbar_expect(sb + B_X + 8 * b, 16384);
          tma2d(sb + HB + b * 16384, &m_x, 64 * b, 128 * r, sb + B_X + 8 * b);
        }
      }
      __syncwarp();
      TS(2, 21);
      asm volatile("bar.sync 4, 64;\n" ::: "memory");
      if (elect_one()) {
#pragma unroll
        for (int s = 0; s < 6; s++) {
          if (s == WDELAY) mbar_wait(sb + B_X + 8 * XWAIT, 0);
          mbar_expect(sb + B_FULL + 8 * s, SLOT);
          tma2d(sb + s * SLOT, &m_qkv, D_ + cmain, 96 * s, sb + B_FULL + 8 * s);
        }
        const CUtensorMap* mpf = (r & 1) ? &m_w3 : &m_w1;
        if (r < 6) tma2d_prefetch(&m_qkv, 2 * D_ + cmain, 96 * r);
        if (r < 12) { tma2d_prefetch(mpf, 576 * j, 96 * (r >> 1)); tma2d_prefetch(mpf, 576 * j + 32, 96 * (r >> 1)); }
#pragma unroll
        for (int s = 0; s < 6; s++) {
          mbar_wait(sb + B_EMPTY + 8 * s, 0);
          mbar_expect(sb + B_FULL + 8 * s, SLOT);
          tma2d(sb + s * SLOT, &m_qkv, 2 * D_ + cmain, 96 * s, sb + B_FULL + 8 * s);
        }
#pragma unroll 1
        for (int n = 0; n < 18; n++) {
          const int col = 576 * j + 32 * n;
          if (n < 16) { if (r < 12) tma2d_prefetch(mpf, col + 64, 96 * (r >> 1)); }
          else if (r < 6) {
            if (n == 16) tma2d_prefetch(&m_qkv, cmain, 96 * r);
            else tma2d_prefetch(&m_w2, 512, 576 * j + 96 * r);
          }
#pragma unroll
          for (int s = 0; s < 6; s++) {
            mbar_wait(sb + B_EMPTY + 8 * s, (n & 1) ^ 1);
            mbar_expect(sb + B_FULL + 8 * s, SLOT);
            tma2d(sb + s * SLOT, &m_w1, col, 96 * s, sb + B_FULL + 8 * s);
            tma2d(sb + s * SLOT + SLOT / 2, &m_w3, col, 96 * s, sb + B_FULL + 8 * s);
          }
        }
        if (r < 6) tma2d_prefetch(&m_w2, 64 * ((j + 1) & 7), 576 * j + 96 * r);
#pragma unroll
        for (int s = 0; s < 6; s++) {
          mbar_wait(sb + B_EMPTY + 8 * s, 1);
          mbar_expect(sb + B_FULL + 8 * s, SLOT);
          tma2d(sb + s * SLOT, &m_qkv, cmain, 96 * s, sb + B_FULL + 8 * s);
        }
#pragma unroll 1
        for (int n = 0; n < 9; n++) {
          const int col = n == 0 ? 512 : 64 * ((j + n) & 7);
          if (n < 7 && r < 6) tma2d_prefetch(&m_w2, 64 * ((j + n + 2) & 7), 576 * j + 96 * r);
#pragma unroll
          for (int s = 0; s < 6; s++) {
            mbar_wait(sb + B_EMPTY + 8 * s, n & 1);
            mbar_expect(sb + B_FULL + 8 * s, SLOT);
            tma2d(sb + s * SLOT, &m_w2, col, 576 * j + 96 * s, sb + B_FULL + 8 * s);
          }
          if (n == 0) {
            mbar_wait(sb + B_HFREE, 0);
            mbar_wait(sb + B_MRDY, 0);
            asm volatile("fence.proxy.async;\n" ::: "memory");
          }
          mbar_wait(sb + B_EMPTY + 48, (n & 1) ^ 1);
          mbar_expect(sb + B_FULL + 48, 80 * 128);
          tma2d(sb + WO_SLOT, &m_M, col, 80 * j, sb + B_FULL + 48);
          if (n == 4) {
            mbar_expect(sb + B_X, 16384);
            tma2d(sb + XT, &m_x, 64 * j, 128 * r, sb + B_X);
          }
        }
      }
    } else {
      const int ht = tid - 288;
      if (warp == 9) {
        if (elect_one()) {
          asm volatile("prefetch.tensormap [%0];\n" ::"l"(&m_qkv) : "memory");
#pragma unroll
          for (int i = 9; i < 29; i++) mbar_init(sb + BARS + 8 * i, i < 16 ? 1 : i < 26 ? 8 : i == 26 ? 4 : 96);
          asm volatile("fence.mbarrier_init.release.cluster;\n" ::: "memory");
        }
        __syncwarp();
        asm volatile("bar.arrive 4, 64;\n" ::: "memory");
      }
      asm volatile("bar.sync 0, 384;\n" ::: "memory");
      const uint32_t ep = g_epoch[blockIdx.x] + 1;
      mbar_wait(sb + B_X + 8 * 8, 0);
      if (ht < 90) {
        const int e = ht / 18, c = ht - e * 18;
        const __nv_bfloat16* w = p.wo + (size_t)(72 * j + 18 * (r >> 2) + e) * D_ + 144 * (r & 3) + c * 8;
#pragma unroll
        for (int i = 0; i < 4; i++)
          if (i < 3 || ht < 54) cp_async16(sb + WOB + ht * 16 + i * 90 * 16, w + i * 5 * D_);
      }
      const __nv_bfloat16* wl = p.wqkv + (size_t)ht * (3 * D_) + 72 * j + ((j & 1) ? 0 : 64);
      mbar_wait(sb + B_XDONE, 0);
#pragma unroll
      for (int g = 0; g < 3; g++)
#pragma unroll
        for (int m = 0; m < 6; m++) cp_async16(sb + L24_T + g * 9216 + m * 96 * 16 + ht * 16, wl + (size_t)m * 96 * 3 * D_ + (g == 2 ? 0 : (g + 1) * D_));
      if (ht < 64) {
#pragma unroll
        for (int i = 0; i < 4; i++) sts128(sb + V_T - 2048 + (i >> 1) * 20480 + (i & 1) * 1024 + ht * 16, 0x3F803F80u, 0x3F803F80u, 0x3F803F80u, 0x3F803F80u);
      }
      asm volatile("cp.async.wait_all;\n" ::: "memory");
      fence_async_smem();
      mbar_arrive(sb + B_LFULL);
      if (warp == 9) TS(3, 1);

      if (ht == 0) {
        mbar_wait(sb + B_KVD, 0);
        red_rel(&g_cnt1[j * 32]);
        wait_ge(&g_cnt1[j * 32], 16 * ep);
      }
      bar_sync(3, 96);
      if (warp == 9) TS(3, 4);
#pragma unroll 1
      for (int i = ht; i < 171; i += 96) {
        const int dp = i / 19, el = i - dp * 19, hd = r >> 2, w = hd >> 1;
        const int d = 18 * hd + 2 * dp - 32 * w;
        const int m = el == 18 ? 56 * w : 18 * hd + el + 8 - 24 * w;
        const float2* src = reinterpret_cast<const float2*>(g_kvp + j * 16 * 1280 + ((w * 4 + (m >> 4)) * 5 + (d >> 3)) * 32 + (m & 7) * 4 + ((d & 7) >> 1)) + ((m >> 3) & 1);
        float s0 = 0.f, s1 = 0.f;
#pragma unroll 1
        for (int r4 = 0; r4 < 4; r4++) {
          const float2 v0 = __ldcg(src), v1 = __ldcg(src + 2560), v2 = __ldcg(src + 2 * 2560), v3 = __ldcg(src + 3 * 2560);
          s0 += (v0.x + v1.x) + (v2.x + v3.x);
          s1 += (v0.y + v1.y) + (v2.y + v3.y);
          src += 4 * 2560;
        }
        sts64(sb + KVS + dp * 160 + el * 8, __float_as_uint(s0), __float_as_uint(s1));
        if ((r & 3) == 0 && el == 18) *reinterpret_cast<float2*>(g_z + j * 72 + hd * 18 + dp * 2) = make_float2(s0, s1);
      }
      bar_sync(3, 96);
      if (warp == 9) TS(3, 5);
#pragma unroll 1
      for (int t = ht; t < 648; t += 96) {
        const int dp = t / 72, cp = t - dp * 72;
        float c0 = 0.f, c1 = 0.f, c2 = 0.f, c3 = 0.f;
        const uint32_t ka = sb + KVS + dp * 160, wa = sb + WOB + cp * 4;
#pragma unroll
        for (int e2 = 0; e2 < 9; e2++) {
          uint32_t a0, a1, a2, a3;
          lds128(a0, a1, a2, a3, ka + e2 * 16);
          const uint32_t w0 = lds32(wa + e2 * 576), w1 = lds32(wa + e2 * 576 + 288);
          c0 = fmaf(__uint_as_float(a0), blo(w0), c0); c1 = fmaf(__uint_as_float(a0), bhi(w0), c1);
          c2 = fmaf(__uint_as_float(a1), blo(w0), c2); c3 = fmaf(__uint_as_float(a1), bhi(w0), c3);
          c0 = fmaf(__uint_as_float(a2), blo(w1), c0); c1 = fmaf(__uint_as_float(a2), bhi(w1), c1);
          c2 = fmaf(__uint_as_float(a3), blo(w1), c2); c3 = fmaf(__uint_as_float(a3), bhi(w1), c3);
        }
        const int d = 18 * (r >> 2) + 2 * dp;
        uint32_t* dst = reinterpret_cast<uint32_t*>(g_M) + (80 * j + ((j & 1) ? (d < 8 ? d + 64 : d - 8) : d)) * 288 + 72 * (r & 3) + cp;
        dst[0] = pack2(c0, c1);
        dst[288] = pack2(c2, c3);
      }
      asm volatile("fence.proxy.async;\n" ::: "memory");
      bar_sync(3, 96);
      if (warp == 9) TS(3, 6);
      if (ht == 0) { red_rel(&g_cnt2[j * 32]); wait_ge(&g_cnt2[j * 32], 16 * ep); }
      bar_sync(3, 96);
      if (ht < 80) {
        const int d = (j & 1) ? (ht < 64 ? ht + 8 : ht - 64) : ht;
        uint32_t zb = 0;
        if (ht < 72) zb = pack2(__ldcg(g_z + j * 72 + d), 0.f);
        const int hd = d / 18;
        const uint32_t w = (hd & 1) ? zb << 16 : zb;
        const uint32_t w0 = hd < 2 ? w : 0u, w1 = hd < 2 ? 0u : w;
        sts128(sb + ZM + ht * 16, w0, w0, w0, w0);
        sts128(sb + ZM + 1280 + ht * 16, w1, w1, w1, w1);
      }
      const uint32_t tag = (ep & 1) << 16;
      if (ht == 95) { sts32(sb + TAGW, tag); g_epoch[blockIdx.x] = ep; }
      fence_async_smem();
      mbar_arrive(sb + B_MRDY);
      if (warp == 9) TS(3, 7);
      if (warp < 11) {
        mbar_wait(sb + B_FULL + 48, 0);
#pragma unroll 1
        for (int i = warp - 9; i < 4; i += 2) {
          const uint4* src = g_part + (size_t)((r * 9 + 8) * 8) * 1024 + j * 128 + i * 32 + lane;
          const int off = ((r * 128 + j * 16 + (lane >> 2)) * D_ + 512 + 16 * i + 2 * (lane & 3)) >> 1;
          float s0, s1, s2, s3, s4, s5, s6, s7;
          {
            const uint32_t* xp = reinterpret_cast<const uint32_t*>(p.x) + off;
            const uint32_t x0 = __ldg(xp), x1 = __ldg(xp + 4 * D_), x2 = __ldg(xp + 4), x3 = __ldg(xp + 4 * D_ + 4);
            s0 = blo(x0); s1 = bhi(x0); s2 = blo(x1); s3 = bhi(x1); s4 = blo(x2); s5 = bhi(x2); s6 = blo(x3); s7 = bhi(x3);
          }
          uint32_t n = 0;
#pragma unroll 1
          for (int jj = 0; jj < 8;) {
            uint32_t v0, v1, v2, v3;
            ld_b128(v0, v1, v2, v3, src);
            if (__all_sync(0xffffffffu, ((v0 ^ tag) & 0x10000u) == 0)) {
              s0 += blo(v0); s1 += __uint_as_float(v0 & 0xfffe0000u); s2 += blo(v1); s3 += bhi(v1);
              s4 += blo(v2); s5 += bhi(v2); s6 += blo(v3); s7 += bhi(v3);
              jj++;
              src += 1024;
            } else {
              __nanosleep(200);
              if (++n > SPIN_LIMIT) __trap();
            }
          }
          uint32_t* op = reinterpret_cast<uint32_t*>(p.out) + off;
          op[0] = pack2(s0, s1); op[4 * D_] = pack2(s2, s3); op[4] = pack2(s4, s5); op[4 * D_ + 4] = pack2(s6, s7);
        }
        if (warp == 9) TS(3, 10);
      }
    }
  } else {
    asm volatile("setmaxnreg.inc.sync.aligned.u32 240;\n");
    asm volatile("bar.sync 0, 384;\n" ::: "memory");
    const int wg = warp >> 2;
    uint32_t a[36][4];
    float dA[32], dB[32];
    const bool l0 = lane == 0;
    constexpr uint64_t dsw128 = mkdesc(sb, 16, 1024, 1);
    constexpr uint64_t dsw64 = mkdesc(sb, SLOT / 2, 512, 2);

    auto issue = [&](float (&d)[32], const uint64_t dbase, const int kstride, const int s, const uint32_t ph, const int init = 0) {
      mbar_wait(sb + B_FULL + 8 * s, ph);
      wg_fence();
#pragma unroll
      for (int ks = 0; ks < 6; ks++) wgmma_rs64(d, a[s * 6 + ks], dbase + ((s * SLOT + ks * kstride) >> 4), (s | ks | init) != 0);
    };
    auto finish = [&](const int rel) {
      wg_commit();
      wg_wait<1>();
      if (rel >= 0 && l0) mbar_arrive(sb + B_EMPTY + 8 * rel);
    };
    auto stW = [&](float (&d)[32], const int s, const uint32_t ph, const int rel) { issue(d, dsw128, 2048, s, ph); finish(rel); };
    auto stF = [&](float (&d)[32], const int s, const uint32_t ph, const int rel) { issue(d, dsw64, 1024, s, ph); finish(rel); };

    TSC(1);
    uint32_t mb0, mb1;
    float r0, r1;
    auto center = [&](const int g) {
#pragma unroll
      for (int ks = 6 * g; ks < 6 * g + 6; ks++) {
        a[ks][0] = bsub2(a[ks][0], mb0); a[ks][1] = bsub2(a[ks][1], mb1);
        a[ks][2] = bsub2(a[ks][2], mb0); a[ks][3] = bsub2(a[ks][3], mb1);
        asm volatile("" : "+r"(a[ks][0]), "+r"(a[ks][1]), "+r"(a[ks][2]), "+r"(a[ks][3])::"memory");
      }
    };
    {
      const uint32_t xa = sb + HB + (warp * 16 + (lane & 15)) * 128;
      const uint32_t sw = lane & 7, hi = lane >> 4;
      constexpr uint32_t ONES = 0x3F803F80u;
      float cs[2][4], cq[4][4];
#pragma unroll
      for (int i = 0; i < 4; i++) { cs[0][i] = cs[1][i] = cq[0][i] = cq[1][i] = cq[2][i] = cq[3][i] = 0.f; }
      auto gram = [&](const uint32_t (&e)[4]) {
        mma1688(cq[0], e[0], e[1], e[0]); mma1688(cq[1], e[0], e[1], e[1]);
        mma1688(cq[2], e[2], e[3], e[2]); mma1688(cq[3], e[2], e[3], e[3]);
      };
#pragma unroll
      for (int b = 0; b < 9; b++) {
        mbar_wait(sb + B_X + 8 * b, 0);
        if (b == 0 || b == 8) TSC(32 + b);
#pragma unroll
        for (int kk = 0; kk < 4; kk++) ldsm4(a[4 * b + kk][0], a[4 * b + kk][1], a[4 * b + kk][2], a[4 * b + kk][3], xa + b * 16384 + (((2 * kk + hi) ^ sw) << 4));
        if (b > 0) {
#pragma unroll
          for (int ks = 4 * b - 4; ks < 4 * b; ks++) { gram(a[ks]); mma16816(cs[ks & 1], a[ks][0], a[ks][1], a[ks][2], a[ks][3], ONES, ONES); }
        }
      }
#pragma unroll
      for (int ks = 32; ks < 36; ks++) mma16816(cs[ks & 1], a[ks][0], a[ks][1], a[ks][2], a[ks][3], ONES, ONES);
#pragma unroll
      for (int kk = 0; kk < 4; kk++) gram(a[32 + kk]);
      TSC(2);
      const float m0 = (cs[0][0] + cs[1][0]) * (1.f / 576.f), m1 = (cs[0][2] + cs[1][2]) * (1.f / 576.f);
      mb0 = pack2(m0, m0);
      mb1 = pack2(m1, m1);
      center(0);
      TSC(3);
      stW(dA, 0, 0, -1);
      center(1);
      stW(dA, 1, 0, 0);
      const bool godd = lane & 4;
      const int src = (lane & ~3) | (lane >> 3);
      const float q0 = __shfl_sync(0xffffffffu, godd ? cq[0][1] + cq[2][1] : cq[0][0] + cq[2][0], src) * (1.f / 576.f);
      const float q1 = __shfl_sync(0xffffffffu, godd ? cq[1][3] + cq[3][3] : cq[1][2] + cq[3][2], src) * (1.f / 576.f);
      float v0 = q0 - m0 * m0, v1 = q1 - m1 * m1;
      if (__any_sync(0xffffffffu, v0 < q0 * (1.f / 64.f) || v1 < q1 * (1.f / 64.f))) {
        float s0 = 0.f, s1 = 0.f;
#pragma unroll 1
        for (int ks = 0; ks < 36; ks++) {
          uint32_t e0, e1, e2, e3;
          ldsm4(e0, e1, e2, e3, xa + (ks >> 2) * 16384 + (((2 * (ks & 3) + hi) ^ sw) << 4));
          float t;
          t = blo(e0) - m0; s0 = fmaf(t, t, s0); t = bhi(e0) - m0; s0 = fmaf(t, t, s0);
          t = blo(e2) - m0; s0 = fmaf(t, t, s0); t = bhi(e2) - m0; s0 = fmaf(t, t, s0);
          t = blo(e1) - m1; s1 = fmaf(t, t, s1); t = bhi(e1) - m1; s1 = fmaf(t, t, s1);
          t = blo(e3) - m1; s1 = fmaf(t, t, s1); t = bhi(e3) - m1; s1 = fmaf(t, t, s1);
        }
        s0 += __shfl_xor_sync(0xffffffffu, s0, 1); s1 += __shfl_xor_sync(0xffffffffu, s1, 1);
        s0 += __shfl_xor_sync(0xffffffffu, s0, 2); s1 += __shfl_xor_sync(0xffffffffu, s1, 2);
        v0 = s0 * (1.f / 576.f); v1 = s1 * (1.f / 576.f);
      }
      __syncwarp();
      if (l0) mbar_arrive(sb + B_XDONE);
      r0 = rcp(rbf(sqrta(rbf(rbf(fmaxf(v0, 0.f)) + 1e-5f))));
      r1 = rcp(rbf(sqrta(rbf(rbf(fmaxf(v1, 0.f)) + 1e-5f))));
    }
#pragma unroll
    for (int s = 2; s < 6; s++) {
      center(s);
      stW(dA, s, 0, s - 1);
    }
    TSC(4); GT(1);
    constexpr float LOG2E = 1.4426950408889634f;
    float l0e = r0 * LOG2E, l1e = r1 * LOG2E;
    const uint32_t tile_off = ((lane >> 4) + (j & 1)) * 2048 + (warp * 16 + (lane & 15)) * 16;
    mbar_wait(sb + B_XDONE, 0);
#pragma unroll
    for (int s = 0; s < 6; s++) {
      stW(dB, s, 1, (s + 5) % 6);
      if (s < 4) {
        const int t = 2 * s;
        pin8(dA, 4 * t);
        stsm4(sb + PK_T + tile_off + t * 2048, pack2(phi(dA[4 * t], r0, l0e), phi(dA[4 * t + 1], r0, l0e)), pack2(phi(dA[4 * t + 2], r1, l1e), phi(dA[4 * t + 3], r1, l1e)),
              pack2(phi(dA[4 * t + 4], r0, l0e), phi(dA[4 * t + 5], r0, l0e)), pack2(phi(dA[4 * t + 6], r1, l1e), phi(dA[4 * t + 7], r1, l1e)));
      }
    }
    TSC(5);
    {
#pragma unroll
      for (int s = 0; s < 2; s++) {
        stF(dA, s, 0, (s + 5) % 6);
#pragma unroll
        for (int t = 4 * s; t < 4 * s + 4; t += 2) {
          pin8(dB, 4 * t);
          stsm4(sb + V_T + tile_off + t * 2048, pack2(dB[4 * t] * r0, dB[4 * t + 1] * r0), pack2(dB[4 * t + 2] * r1, dB[4 * t + 3] * r1),
                pack2(dB[4 * t + 4] * r0, dB[4 * t + 5] * r0), pack2(dB[4 * t + 6] * r1, dB[4 * t + 7] * r1));
        }
      }
      float dL[12];
      constexpr uint64_t dl = mkdesc(sb + L24_T, 128, 576 * 16, 0);
      mbar_wait(sb + B_LFULL, 0);
#pragma unroll
      for (int s = 2; s < 5; s++) {
        mbar_wait(sb + B_FULL + 8 * s, 0);
        wg_fence();
#pragma unroll
        for (int ks = 12 * (s - 2); ks < 12 * (s - 1); ks++) wgmma_rs24(dL, a[ks], dl + ks * 16, ks != 0);
#pragma unroll
        for (int ks = 0; ks < 6; ks++) wgmma_rs64(dA, a[s * 6 + ks], dsw64 + ((s * SLOT + ks * 1024) >> 4), 1);
        finish(s - 1);
      }
      stF(dA, 5, 0, 4);
      pin(dL);
      const uint32_t lo = ((j & 1) ? 0 : 8 * 2048) + warp * 256 + lane * 4;
      sts32(sb + PK_T + lo, pack2(phi(dL[0], r0, l0e), phi(dL[1], r0, l0e)));
      sts32(sb + PK_T + lo + 128, pack2(phi(dL[2], r1, l1e), phi(dL[3], r1, l1e)));
      sts32(sb + V_T + lo, pack2(dL[4] * r0, dL[5] * r0));
      sts32(sb + V_T + lo + 128, pack2(dL[6] * r1, dL[7] * r1));
      sts64(sb + Q8 + tid * 8, pack2(dL[8], dL[9]), pack2(dL[10], dL[11]));
      fence_async_smem();
      __syncwarp();
      if (l0) mbar_arrive(sb + B_KVT);
    }
    TSC(6);
    uint32_t hs = sb + HB + wg * HHALF + (tid & 127) * 16;
    uint32_t hp0, hp1;
    const float iq0 = rcp(r0 * r0), iq1 = rcp(r1 * r1);
    auto epiF = [&](float (&d)[32], const int pc) {
      asm volatile("" : "+f"(d[4 * pc]), "+f"(d[4 * pc + 1]), "+f"(d[4 * pc + 2]), "+f"(d[4 * pc + 3]), "+f"(d[4 * pc + 16]), "+f"(d[4 * pc + 17]),
                   "+f"(d[4 * pc + 18]), "+f"(d[4 * pc + 19])::"memory");
      const float g0 = d[4 * pc], g1 = d[4 * pc + 1], g2 = d[4 * pc + 2], g3 = d[4 * pc + 3];
      const uint32_t h0 = pack2(g0 * d[4 * pc + 16] * rcp(fmaf(ex2(-g0 * l0e), iq0, iq0)), g1 * d[4 * pc + 17] * rcp(fmaf(ex2(-g1 * l0e), iq0, iq0)));
      const uint32_t h1 = pack2(g2 * d[4 * pc + 18] * rcp(fmaf(ex2(-g2 * l1e), iq1, iq1)), g3 * d[4 * pc + 19] * rcp(fmaf(ex2(-g3 * l1e), iq1, iq1)));
      if (pc & 1) {
        sts128(hs, hp0, hp1, h0, h1);
        hs += 2048;
      } else {
        hp0 = h0; hp1 = h1;
        asm volatile("" : "+r"(hp0), "+r"(hp1)::"memory");
      }
    };
    {
      stF(dB, 0, 1, 5);
      epiF(dA, 0); epiF(dA, 1);
      stF(dB, 1, 1, 0);
      epiF(dA, 2); epiF(dA, 3);
      float dK[20];
      const uint64_t ka = mkdesc(sb + V_T - 2048 + wg * 3 * 2048, 128, 2048, 0), kb = mkdesc(sb + PK_T + wg * 4 * 2048, 128, 2048, 0);
      mbar_wait(sb + B_KVT, 0);
      mbar_wait(sb + B_FULL + 8 * 2, 1);
      wg_fence();
#pragma unroll
      for (int ks = 0; ks < 8; ks++) wgmma_ss40tt(dK, ka + ks * 16, kb + ks * 16, ks != 0);
#pragma unroll
      for (int ks = 0; ks < 6; ks++) wgmma_rs64(dB, a[12 + ks], dsw64 + ((2 * SLOT + ks * 1024) >> 4), 1);
      finish(1);
      stF(dB, 3, 1, 2);
      pin(dK);
      float4* dst = g_kvp + (j * 16 + r) * 1280 + warp * 160 + lane;
#pragma unroll
      for (int t = 0; t < 5; t++) __stcg(dst + t * 32, make_float4(dK[4 * t], dK[4 * t + 1], dK[4 * t + 2], dK[4 * t + 3]));
      __syncwarp();
      if (l0) mbar_arrive(sb + B_KVD);
      stF(dB, 4, 1, 3);
    }
#pragma unroll 1
    for (int it = 0; it < 8; it++) {
      stF(dB, 5, 1, 4);
      stF(dA, 0, 0, 5);
#pragma unroll
      for (int s = 1; s < 5; s++) { epiF(dB, s - 1); stF(dA, s, 0, s - 1); }
      stF(dA, 5, 0, 4);
      stF(dB, 0, 1, 5);
#pragma unroll
      for (int s = 1; s < 5; s++) { epiF(dA, s - 1); stF(dB, s, 1, s - 1); }
      TSC(7 + it);
    }
    stF(dB, 5, 1, 4);
    TSC(15);
    const uint32_t hl = sb + HB + wg * HHALF + (tid & 127) * 16;
    auto reload = [&](auto k0, auto k1) {
      static_for<decltype(k0)::value, decltype(k1)::value>([&](auto k) { lds128_inplace<decltype(k)::value * 2048>(a[decltype(k)::value], hl); });
    };
    stW(dA, 0, 0, 5);
    epiF(dB, 0);
    stW(dA, 1, 0, 0);
    reload(IC<0>(), IC<4>());
    epiF(dB, 1);
    stW(dA, 2, 0, 1);
    reload(IC<4>(), IC<8>());
    epiF(dB, 2);
    stW(dA, 3, 0, 2);
    reload(IC<8>(), IC<12>());
    __syncwarp();
    if (l0 && wg == 0) mbar_arrive(sb + B_HFREE);
    epiF(dB, 3);
    stW(dA, 4, 0, 3);
    reload(IC<12>(), IC<17>());
    stW(dA, 5, 0, 4);
    reload(IC<17>(), IC<22>());
    const uint32_t ot = sb + HB + wg * HHALF;
    const uint32_t do_a = (uint32_t)mkdesc(ot, 128, 1280, 0);
    constexpr uint64_t do_b = mkdesc(sb + WO_SLOT, 16, 1024, 1);
    auto stO = [&](float (&d)[32], const uint32_t ph, const int rel) {
      mbar_wait(sb + B_FULL + 48, ph);
      wg_fence();
      wgmma_ss64<0, 80>(d, do_a, do_b);
      wgmma_ss64<16, 80>(d, do_a, do_b + 128);
      wgmma_ss64<32, 80>(d, do_a, do_b + 256);
      wgmma_ss64<48, 80>(d, do_a, do_b + 384);
      wgmma_ss64<64, 80>(d, do_a, do_b + 512);
      finish(rel);
    };
    uint32_t tag;
    auto epiP = [&](float (&d)[32], const int step) {
      pin(d);
      const int c = step == 0 ? 8 : ((j + step) & 7);
      uint4* dst = g_part + (size_t)((r * 9 + c) * 8 + j) * 1024 + warp * 128 + lane;
#pragma unroll
      for (int i = 0; i < 4; i++)
        st_b128(dst + i * 32, (pack2(d[8 * i], d[8 * i + 1]) & 0xfffeffffu) | tag, pack2(d[8 * i + 2], d[8 * i + 3]), pack2(d[8 * i + 4], d[8 * i + 5]), pack2(d[8 * i + 6], d[8 * i + 7]));
    };
    TSC(16);
    {
      stW(dB, 0, 1, 5);
      reload(IC<22>(), IC<26>());
      asm volatile("" : "+f"(l0e), "+f"(l1e));
      r0 = l0e * (1.f / LOG2E); r1 = l1e * (1.f / LOG2E);
      uint32_t pq[18];
      const uint32_t oa = ot + ((warp & 3) * 2 + ((lane >> 3) & 1)) * 1280 + (lane >> 4) * 128 + (lane & 7) * 16;
      auto phiq = [&](const int t0, const int t1) {
#pragma unroll
        for (int t = t0; t < t1; t++) {
          asm volatile("" : "+f"(dA[4 * t]), "+f"(dA[4 * t + 1]), "+f"(dA[4 * t + 2]), "+f"(dA[4 * t + 3])::"memory");
          pq[2 * t] = pack2(phi(dA[4 * t], r0, l0e), phi(dA[4 * t + 1], r0, l0e));
          pq[2 * t + 1] = pack2(phi(dA[4 * t + 2], r1, l1e), phi(dA[4 * t + 3], r1, l1e));
          asm volatile("" : "+r"(pq[2 * t]), "+r"(pq[2 * t + 1])::"memory");
        }
      };
      phiq(0, 3);
      bar_sync(1 + wg, 128);
      stW(dB, 1, 1, 0);
      reload(IC<26>(), IC<30>());
      phiq(3, 6);
      stW(dB, 2, 1, 1);
      phiq(6, 8);
      {
        uint32_t q0, q1;
        lds64(q0, q1, sb + Q8 + tid * 8);
        pq[16] = pack2(phi(blo(q0), r0, l0e), phi(bhi(q0), r0, l0e));
        pq[17] = pack2(phi(blo(q1), r1, l1e), phi(bhi(q1), r1, l1e));
      }
#pragma unroll
      for (int t = 0; t < 8; t += 2) stsm4(oa + t * 128, pq[2 * t], pq[2 * t + 1], pq[2 * t + 2], pq[2 * t + 3]);
      stsm4(oa + 1024, pq[16], pq[17], 0u, 0u);
      fence_async_smem();
      TSC(17);
      mbar_wait(sb + B_MRDY, 0);
      TSC(18);
      tag = lds32(sb + TAGW);
      float den[8];
      constexpr uint64_t dz = mkdesc(sb + ZM, 128, 1280, 0);
      bar_sync(1 + wg, 128);
      issue(dB, dsw128, 2048, 3, 1);
      wgmma_ss16<0, 80, 0>(den, do_a, dz);
      wgmma_ss16<16, 80, 1>(den, do_a, dz + 16);
      wgmma_ss16<32, 80, 1>(den, do_a, dz + 32);
      wgmma_ss16<48, 80, 1>(den, do_a, dz + 48);
      wgmma_ss16<64, 80, 1>(den, do_a, dz + 64);
      finish(2);
      reload(IC<30>(), IC<36>());
      stW(dB, 4, 1, 3);
      pin(den);
      uint32_t iv[8];
#pragma unroll
      for (int i = 0; i < 8; i++) { const float t = rcp(den[i] + 1e-6f); iv[i] = pack2(t, t); }
      const int u = 2 * (lane & 3) + 8 * (j & 1);
#pragma unroll
      for (int t = 0; t < 10; t += 2) {
        uint32_t o[4];
#pragma unroll
        for (int z = 0; z < 2; z++) {
          const int tt = t + z;
          if (tt < 9) {
            const int lo = tt == 0 ? 0 : tt >= 7 ? 3 : (tt - 1) >> 1, hi = tt == 8 ? 0 : (tt == 0 || tt == 7) ? lo : lo + 1;
            const bool up = tt == 8 ? (j & 1) : 8 * tt + u >= 18 * hi;
            const int il = (lo >> 1) * 4 + (lo & 1), ih = (hi >> 1) * 4 + (hi & 1);
            o[2 * z] = bmul2(pq[2 * tt], up ? iv[ih] : iv[il]);
            o[2 * z + 1] = bmul2(pq[2 * tt + 1], up ? iv[ih + 2] : iv[il + 2]);
          } else {
            o[2 * z] = 0; o[2 * z + 1] = 0;
          }
        }
        stsm4(oa + t * 128, o[0], o[1], o[2], o[3]);
      }
      fence_async_smem();
      stW(dB, 5, 1, 4);
      bar_sync(1 + wg, 128);
      stO(dB, 0, 5);
    }
    stW(dA, 0, 0, 6);
    epiP(dB, 0);
    TSC(19);
    auto ldp = [&](uint32_t (&v)[16], const int c, const int dj) {
      const uint4* src = g_part + (size_t)((r * 9 + c) * 8 + ((j + dj) & 7)) * 1024 + warp * 128 + lane;
#pragma unroll
      for (int i = 0; i < 4; i++) ld_b128(v[4 * i], v[4 * i + 1], v[4 * i + 2], v[4 * i + 3], src + i * 32);
    };
    auto chk = [&](uint32_t (&v)[16], const int c, const int dj) {
      uint32_t n = 0;
      while (__any_sync(0xffffffffu, (((v[0] ^ tag) | (v[4] ^ tag) | (v[8] ^ tag) | (v[12] ^ tag)) & 0x10000u) != 0)) {
        ldp(v, c, dj);
        if (++n > SPIN_LIMIT) asm volatile("trap;");
      }
    };
    auto unp = [&](float (&d)[32], uint32_t (&v)[16], const int i) {
      d[8 * i] = blo(v[4 * i]); d[8 * i + 1] = __uint_as_float(v[4 * i] & 0xfffe0000u); d[8 * i + 2] = blo(v[4 * i + 1]); d[8 * i + 3] = bhi(v[4 * i + 1]);
      d[8 * i + 4] = blo(v[4 * i + 2]); d[8 * i + 5] = bhi(v[4 * i + 2]); d[8 * i + 6] = blo(v[4 * i + 3]); d[8 * i + 7] = bhi(v[4 * i + 3]);
      pin8(d, 8 * i);
    };
#pragma unroll
    for (int s = 1; s < 6; s++) stW(dA, s, 0, s - 1);
    stO(dA, 1, 5);
    stW(dB, 0, 1, 6);
    epiP(dA, 1);
    TSC(20);
#pragma unroll 1
    for (int it = 0; it < 3; it++) {
      uint32_t v[16];
      stW(dB, 1, 1, 0);
#pragma unroll
      for (int i = 0; i < 16; i++) v[i] = (i & 3) ? 0u : tag;
      if (it > 0) ldp(v, (j + 3 + 2 * it) & 7, 3);
      stW(dB, 2, 1, 1);
      stW(dB, 3, 1, 2);
      stW(dB, 4, 1, 3);
      chk(v, (j + 3 + 2 * it) & 7, 3);
      unp(dA, v, 0); unp(dA, v, 1);
      stW(dB, 5, 1, 4);
      unp(dA, v, 2); unp(dA, v, 3);
      stO(dB, 0, 5);
      issue(dA, dsw128, 2048, 0, 0, 1); finish(6);
      epiP(dB, 2 + 2 * it);
      stW(dA, 1, 0, 0);
      ldp(v, (j + 4 + 2 * it) & 7, 3);
      stW(dA, 2, 0, 1);
      stW(dA, 3, 0, 2);
      stW(dA, 4, 0, 3);
      chk(v, (j + 4 + 2 * it) & 7, 3);
      unp(dB, v, 0); unp(dB, v, 1);
      stW(dA, 5, 0, 4);
      unp(dB, v, 2); unp(dB, v, 3);
      stO(dA, 1, 5);
      issue(dB, dsw128, 2048, 0, 1, 1); finish(6);
      epiP(dA, 3 + 2 * it);
      TSC(21 + it);
    }
    {
      uint32_t v[16], w[16], xv[16];
      float f[32] = {};
      auto addv = [&](uint32_t (&v)[16], const int i) {
        f[8 * i] += blo(v[4 * i]); f[8 * i + 1] += __uint_as_float(v[4 * i] & 0xfffe0000u); f[8 * i + 2] += blo(v[4 * i + 1]); f[8 * i + 3] += bhi(v[4 * i + 1]);
        f[8 * i + 4] += blo(v[4 * i + 2]); f[8 * i + 5] += bhi(v[4 * i + 2]); f[8 * i + 6] += blo(v[4 * i + 3]); f[8 * i + 7] += bhi(v[4 * i + 3]);
        pin8(f, 8 * i);
      };
      stW(dB, 1, 1, -1);
      ldp(v, j, 2);
      mbar_wait(sb + B_X, 1);
#pragma unroll
      for (int i = 0; i < 4; i++)
        ldsm4(xv[4 * i], xv[4 * i + 1], xv[4 * i + 2], xv[4 * i + 3], sb + XT + (warp * 16 + (lane & 15)) * 128 + (((2 * i + (lane >> 4)) ^ (lane & 7)) << 4));
      stW(dB, 2, 1, -1);
#pragma unroll
      for (int i = 0; i < 16; i++) { f[2 * i] = blo(xv[i]); f[2 * i + 1] = bhi(xv[i]); }
      pin(f);
      stW(dB, 3, 1, -1);
      ldp(w, j, 1);
      stW(dB, 4, 1, -1);
      chk(v, j, 2);
      addv(v, 0); addv(v, 1);
      stW(dB, 5, 1, -1);
      addv(v, 2); addv(v, 3);
      stO(dB, 0, -1);
      TSC(24);
      chk(w, j, 1);
      addv(w, 0); addv(w, 1); addv(w, 2); addv(w, 3);
      TSC(25);
      wg_wait<0>();
      TSC(26); GT(2);
      pin(dB);
      const uint32_t ps = sb + HB + wg * HHALF + STG + (warp & 3) * 2048;
      const int row = lane & 15;
#pragma unroll
      for (int t = 0; t < 8; t += 2)
        stsm4(ps + row * 128 + (((t + (lane >> 4)) ^ (row & 7)) << 4),
              pack2(f[4 * t] + dB[4 * t], f[4 * t + 1] + dB[4 * t + 1]), pack2(f[4 * t + 2] + dB[4 * t + 2], f[4 * t + 3] + dB[4 * t + 3]),
              pack2(f[4 * t + 4] + dB[4 * t + 4], f[4 * t + 5] + dB[4 * t + 5]), pack2(f[4 * t + 6] + dB[4 * t + 6], f[4 * t + 7] + dB[4 * t + 7]));
      __syncwarp();
#pragma unroll
      for (int i = 0; i < 4; i++) {
        const int rr = i * 4 + (lane >> 3), ch = lane & 7;
        uint4 o;
        lds128(o.x, o.y, o.z, o.w, ps + rr * 128 + ((ch ^ (rr & 7)) << 4));
        *reinterpret_cast<uint4*>(p.out + (size_t)(r * 128 + warp * 16 + rr) * D_ + 64 * j + ch * 8) = o;
      }
    }
    TSC(27); GT(3);
  }
}

typedef CUresult (*EncodeFn)(CUtensorMap*, CUtensorMapDataType, cuuint32_t, void*, const cuuint64_t*, const cuuint64_t*, const cuuint32_t*,
                             const cuuint32_t*, CUtensorMapInterleave, CUtensorMapSwizzle, CUtensorMapL2promotion, CUtensorMapFloatOOBfill);

CUtensorMap make_map(EncodeFn enc, const void* ptr, int rows, int cols, int brow, int bcol, CUtensorMapSwizzle sw) {
  CUtensorMap m;
  cuuint64_t gd[2] = {(cuuint64_t)cols, (cuuint64_t)rows};
  cuuint64_t gs[1] = {(cuuint64_t)cols * 2};
  cuuint32_t bd[2] = {(cuuint32_t)bcol, (cuuint32_t)brow};
  cuuint32_t es[2] = {1, 1};
  enc(&m, CU_TENSOR_MAP_DATA_TYPE_BFLOAT16, 2, const_cast<void*>(ptr), gd, gs, bd, es, CU_TENSOR_MAP_INTERLEAVE_NONE, sw,
      CU_TENSOR_MAP_L2_PROMOTION_L2_128B, CU_TENSOR_MAP_FLOAT_OOB_FILL_NONE);
  return m;
}

}

extern "C" void kernel_launch(void* const* d_in, const int* in_sizes, int n_in, void* d_out, int out_size) {
  (void)in_sizes; (void)n_in; (void)out_size;
  static EncodeFn enc = nullptr;
  static void* m_ptr = nullptr;
  if (!enc) {
    cudaGetSymbolAddress(&m_ptr, g_M);
    cudaDriverEntryPointQueryResult qr;
    cudaGetDriverEntryPoint("cuTensorMapEncodeTiled", (void**)&enc, cudaEnableDefault, &qr);
    cudaFuncSetAttribute(fused_block_kernel, cudaFuncAttributeMaxDynamicSharedMemorySize, SMEM_BYTES);
  }
  Params p;
  p.x = (const __nv_bfloat16*)d_in[0];
  p.wqkv = (const __nv_bfloat16*)d_in[1];
  p.wo = (const __nv_bfloat16*)d_in[2];
  p.w1 = (const __nv_bfloat16*)d_in[4];
  p.w3 = (const __nv_bfloat16*)d_in[5];
  p.w2 = (const __nv_bfloat16*)d_in[6];
  p.out = (__nv_bfloat16*)d_out;
  const CUtensorMap m_qkv = make_map(enc, p.wqkv, D_, 3 * D_, 96, 64, CU_TENSOR_MAP_SWIZZLE_128B);
  const CUtensorMap m_w1 = make_map(enc, p.w1, D_, F_, 96, 32, CU_TENSOR_MAP_SWIZZLE_64B);
  const CUtensorMap m_w3 = make_map(enc, p.w3, D_, F_, 96, 32, CU_TENSOR_MAP_SWIZZLE_64B);
  const CUtensorMap m_w2 = make_map(enc, p.w2, F_, D_, 96, 64, CU_TENSOR_MAP_SWIZZLE_128B);
  const CUtensorMap m_M = make_map(enc, m_ptr, 8 * 80, D_, 80, 64, CU_TENSOR_MAP_SWIZZLE_128B);
  const CUtensorMap m_x = make_map(enc, p.x, 2048, D_, 128, 64, CU_TENSOR_MAP_SWIZZLE_128B);
  fused_block_kernel<<<128, NTHREADS, SMEM_BYTES>>>(m_qkv, m_w1, m_w3, m_w2, m_M, m_x, p);
}
```

```cpp
#include <cuda_runtime.h>
#include <cuda.h>
#include <cuda_bf16.h>
#include <stdint.h>

namespace {

constexpr int D_ = 576, F_ = 4608;
constexpr int NTHREADS = 384;

constexpr uint32_t SLOT = 12288;
constexpr uint32_t HB = 6 * SLOT;
constexpr uint32_t HHALF = 73728;
constexpr uint32_t PK_T = HB + 45056;
constexpr uint32_t V_T = HB + HHALF + 18432;
constexpr uint32_t L24_T = HB + 16384;
constexpr uint32_t WO_SLOT = HB + 12288;
constexpr uint32_t XT = HB + 24576;
constexpr uint32_t STG = 49152;
constexpr uint32_t Q8 = HB + 2 * HHALF;
constexpr uint32_t WOB = Q8 + 2048;
constexpr uint32_t KVS = WOB + 5184;
constexpr uint32_t ZM = WOB;
constexpr uint32_t TAGW = KVS + 1440;
constexpr uint32_t BARS = TAGW + 32;
constexpr uint32_t SMEM_BYTES = BARS + 512;

constexpr uint32_t B_X = BARS;
constexpr uint32_t B_FULL = BARS + 8 * 9;
constexpr uint32_t B_EMPTY = BARS + 8 * 16;
constexpr uint32_t B_XDONE = BARS + 8 * 23;
constexpr uint32_t B_KVT = BARS + 8 * 24;
constexpr uint32_t B_KVD = BARS + 8 * 25;
constexpr uint32_t B_HFREE = BARS + 8 * 26;
constexpr uint32_t B_LFULL = BARS + 8 * 27;
constexpr uint32_t B_MRDY = BARS + 8 * 28;

#define XPF 4
#define WDELAY 2
#define XWAIT 8
constexpr uint32_t SPIN_LIMIT = 1u << 22;

__device__ uint4 g_part[16 * 9 * 8 * 1024];
__device__ float4 g_kvp[8 * 16 * 1280];
__device__ __align__(128) __nv_bfloat16 g_M[8 * 80 * 576];
__device__ __align__(16) float g_z[8 * 72];
__device__ uint32_t g_cnt1[8 * 32], g_cnt2[8 * 32];
__device__ uint32_t g_epoch[128];

#define TS(slot, i)
#define TSC(i)
#define GT(i)

__device__ __forceinline__ void wg_fence() { asm volatile("wgmma.fence.sync.aligned;\n" ::: "memory"); }
__device__ __forceinline__ void wg_commit() { asm volatile("wgmma.commit_group.sync.aligned;\n" ::: "memory"); }
template <int N> __device__ __forceinline__ void wg_wait() { asm volatile("wgmma.wait_group.sync.aligned %0;\n" ::"n"(N) : "memory"); }
__host__ __device__ constexpr uint64_t mkdesc(uint32_t addr, uint32_t lbo, uint32_t sbo, uint32_t sw) {
  return (uint64_t)((addr & 0x3FFFF) >> 4) | ((uint64_t)(lbo >> 4) << 16) | ((uint64_t)(sbo >> 4) << 32) | ((uint64_t)sw << 62);
}
__device__ __forceinline__ void mbar_init(uint32_t a, uint32_t c) { asm volatile("mbarrier.init.shared::cta.b64 [%0], %1;\n" ::"r"(a), "r"(c) : "memory"); }
__device__ __forceinline__ void mbar_expect(uint32_t a, uint32_t b) { asm volatile("mbarrier.arrive.expect_tx.shared::cta.b64 _, [%0], %1;\n" ::"r"(a), "r"(b) : "memory"); }
__device__ __forceinline__ void mbar_arrive(uint32_t a) { asm volatile("mbarrier.arrive.shared::cta.b64 _, [%0];\n" ::"r"(a) : "memory"); }
__device__ __forceinline__ void mbar_wait(uint32_t a, uint32_t ph) {
  asm volatile(
      "{\n.reg .pred p;\n.reg .u32 n;\n"
      "mov.u32 n, 0;\n"
      "LOOP:\n"
      "mbarrier.try_wait.parity.shared::cta.b64 p, [%0], %1;\n"
      "@p bra DONE;\n"
      "add.u32 n, n, 1;\n"
      "setp.gt.u32 p, n, %2;\n"
      "@p trap;\n"
      "bra LOOP;\n"
      "DONE:\n}\n" ::"r"(a), "r"(ph), "n"(SPIN_LIMIT) : "memory");
}
__device__ __forceinline__ void cp_async16(uint32_t dst, const void* src) {
  asm volatile("cp.async.cg.shared.global [%0], [%1], 16;\n" ::"r"(dst), "l"(src) : "memory");
}
__device__ __forceinline__ void tma2d(uint32_t dst, const CUtensorMap* m, int c0, int c1, uint32_t bar) {
  asm volatile("cp.async.bulk.tensor.2d.shared::cluster.global.mbarrier::complete_tx::bytes [%0], [%1, {%3, %4}], [%2];\n" ::"r"(dst), "l"(m), "r"(bar), "r"(c0), "r"(c1) : "memory");
}
__device__ __forceinline__ void tma2d_prefetch(const CUtensorMap* m, int c0, int c1) {
  asm volatile("cp.async.bulk.prefetch.tensor.2d.L2.global [%0, {%1, %2}];\n" ::"l"(m), "r"(c0), "r"(c1) : "memory");
}
__device__ __forceinline__ void fence_async_smem() { asm volatile("fence.proxy.async.shared::cta;\n" ::: "memory"); }
__device__ __forceinline__ void bar_sync(int id, int n) { asm volatile("bar.sync %0, %1;\n" ::"r"(id), "r"(n) : "memory"); }
__device__ __forceinline__ void ldsm4(uint32_t& r0, uint32_t& r1, uint32_t& r2, uint32_t& r3, uint32_t a) {
  asm volatile("ldmatrix.sync.aligned.m8n8.x4.shared.b16 {%0,%1,%2,%3}, [%4];\n" : "=r"(r0), "=r"(r1), "=r"(r2), "=r"(r3) : "r"(a) : "memory");
}
__device__ __forceinline__ void stsm4(uint32_t a, uint32_t r0, uint32_t r1, uint32_t r2, uint32_t r3) {
  asm volatile("stmatrix.sync.aligned.m8n8.x4.shared.b16 [%0], {%1,%2,%3,%4};\n" ::"r"(a), "r"(r0), "r"(r1), "r"(r2), "r"(r3) : "memory");
}
__device__ __forceinline__ void sts128(uint32_t a, uint32_t r0, uint32_t r1, uint32_t r2, uint32_t r3) {
  asm volatile("st.shared.v4.b32 [%0], {%1,%2,%3,%4};\n" ::"r"(a), "r"(r0), "r"(r1), "r"(r2), "r"(r3) : "memory");
}
__device__ __forceinline__ void lds128(uint32_t& r0, uint32_t& r1, uint32_t& r2, uint32_t& r3, uint32_t a) {
  asm volatile("ld.shared.v4.b32 {%0,%1,%2,%3}, [%4];\n" : "=r"(r0), "=r"(r1), "=r"(r2), "=r"(r3) : "r"(a) : "memory");
}
template <int OFF>
__device__ __forceinline__ void lds128_inplace(uint32_t (&r)[4], uint32_t a) {
  asm volatile("{\n.reg .pred p;\nsetp.ne.u32 p, %4, 0;\n@p ld.shared.v4.b32 {%0,%1,%2,%3}, [%4 + %5];\n}\n"
               : "+r"(r[0]), "+r"(r[1]), "+r"(r[2]), "+r"(r[3]) : "r"(a), "n"(OFF) : "memory");
}
__device__ __forceinline__ void sts64(uint32_t a, uint32_t r0, uint32_t r1) { asm volatile("st.shared.v2.b32 [%0], {%1,%2};\n" ::"r"(a), "r"(r0), "r"(r1) : "memory"); }
__device__ __forceinline__ void lds64(uint32_t& r0, uint32_t& r1, uint32_t a) { asm volatile("ld.shared.v2.b32 {%0,%1}, [%2];\n" : "=r"(r0), "=r"(r1) : "r"(a) : "memory"); }
__device__ __forceinline__ uint32_t lds32(uint32_t a) { uint32_t v; asm volatile("ld.shared.b32 %0, [%1];\n" : "=r"(v) : "r"(a) : "memory"); return v; }
__device__ __forceinline__ void sts32(uint32_t a, uint32_t r0) { asm volatile("st.shared.b32 [%0], %1;\n" ::"r"(a), "r"(r0) : "memory"); }
__device__ __forceinline__ void mma16816(float (&c)[4], uint32_t a0, uint32_t a1, uint32_t a2, uint32_t a3, uint32_t b0, uint32_t b1) {
  asm volatile("mma.sync.aligned.m16n8k16.row.col.f32.bf16.bf16.f32 {%0,%1,%2,%3}, {%4,%5,%6,%7}, {%8,%9}, {%0,%1,%2,%3};\n"
               : "+f"(c[0]), "+f"(c[1]), "+f"(c[2]), "+f"(c[3]) : "r"(a0), "r"(a1), "r"(a2), "r"(a3), "r"(b0), "r"(b1));
}
__device__ __forceinline__ uint32_t pack2(float lo, float hi) {
  uint32_t r;
  asm("cvt.rn.bf16x2.f32 %0, %1, %2;\n" : "=r"(r) : "f"(hi), "f"(lo));
  return r;
}
__device__ __forceinline__ float blo(uint32_t w) { return __uint_as_float(w << 16); }
__device__ __forceinline__ float bhi(uint32_t w) { return __uint_as_float(w & 0xffff0000u); }
__device__ __forceinline__ float rbf(float x) { return __bfloat162float(__float2bfloat16_rn(x)); }
__device__ __forceinline__ float ex2(float x) { float r; asm("ex2.approx.ftz.f32 %0, %1;\n" : "=f"(r) : "f"(x)); return r; }
__device__ __forceinline__ float rcp(float x) { float r; asm("rcp.approx.ftz.f32 %0, %1;\n" : "=f"(r) : "f"(x)); return r; }
__device__ __forceinline__ float sqrta(float x) { float r; asm("sqrt.approx.ftz.f32 %0, %1;\n" : "=f"(r) : "f"(x)); return r; }
__device__ __forceinline__ uint32_t bsub2(uint32_t a, uint32_t b) { uint32_t r; asm("sub.rn.bf16x2 %0, %1, %2;\n" : "=r"(r) : "r"(a), "r"(b)); return r; }
__device__ __forceinline__ uint32_t ld_acq(const uint32_t* p) { uint32_t v; asm volatile("ld.acquire.gpu.global.u32 %0, [%1];\n" : "=r"(v) : "l"(p) : "memory"); return v; }
__device__ __forceinline__ void st_b128(void* p, uint32_t a, uint32_t b, uint32_t c, uint32_t d) {
  asm volatile("st.relaxed.gpu.global.v4.b32 [%0], {%1, %2, %3, %4};\n" ::"l"(p), "r"(a), "r"(b), "r"(c), "r"(d) : "memory");
}
__device__ __forceinline__ void ld_b128(uint32_t& a, uint32_t& b, uint32_t& c, uint32_t& d, const void* p) {
  asm volatile("{\n.reg .b128 v;\nld.relaxed.gpu.global.b128 v, [%4];\nmov.b128 {%0, %1, %2, %3}, v;\n}\n" : "=r"(a), "=r"(b), "=r"(c), "=r"(d) : "l"(p) : "memory");
}
__device__ __forceinline__ bool elect_one() {
  uint32_t ok;
  asm volatile("{\n.reg .pred p;\nelect.sync _|p, 0xffffffff;\nselp.u32 %0, 1, 0, p;\n}\n" : "=r"(ok));
  return ok;
}
__device__ __forceinline__ uint32_t bmul2(uint32_t a, uint32_t b) { uint32_t r; asm("mul.rn.bf16x2 %0, %1, %2;\n" : "=r"(r) : "r"(a), "r"(b)); return r; }
__device__ __forceinline__ void red_rel(uint32_t* p) { asm volatile("red.release.gpu.global.add.u32 [%0], 1;\n" ::"l"(p) : "memory"); }
__device__ __forceinline__ void wait_ge(const uint32_t* p, uint32_t target) {
  uint32_t n = 0;
  while ((int32_t)(ld_acq(p) - target) < 0) {
    __nanosleep(64);
    if (++n > SPIN_LIMIT) __trap();
  }
}
__device__ __forceinline__ float phi(float a, float r, float rl) { return fmaf(fmaxf(a, 0.f), r, __saturatef(ex2(a * rl) + 1e-6f)); }

#define ACC8(d, o) "+f"(d[o + 0]), "+f"(d[o + 1]), "+f"(d[o + 2]), "+f"(d[o + 3]), "+f"(d[o + 4]), "+f"(d[o + 5]), "+f"(d[o + 6]), "+f"(d[o + 7])
#define REGS32 "{%0,%1,%2,%3,%4,%5,%6,%7,%8,%9,%10,%11,%12,%13,%14,%15,%16,%17,%18,%19,%20,%21,%22,%23,%24,%25,%26,%27,%28,%29,%30,%31}"
__device__ __forceinline__ void wgmma_rs64(float (&d)[32], const uint32_t (&a)[4], uint64_t db, int acc) {
  asm volatile("{\n.reg .pred p;\nsetp.ne.b32 p, %37, 0;\n"
               "wgmma.mma_async.sync.aligned.m64n64k16.f32.bf16.bf16 " REGS32 ", {%32,%33,%34,%35}, %36, p, 1, 1, 1;\n}\n"
               : ACC8(d, 0), ACC8(d, 8), ACC8(d, 16), ACC8(d, 24)
               : "r"(a[0]), "r"(a[1]), "r"(a[2]), "r"(a[3]), "l"(db), "r"(acc));
}
template <uint32_t OFF, uint32_t HI>
__device__ __forceinline__ void wgmma_ss64(float (&d)[32], uint32_t da_lo, uint64_t db) {
  asm volatile("{\n.reg .b32 lo;\n.reg .b64 da;\nadd.u32 lo, %32, %34;\nmov.b64 da, {lo, %35};\n"
               "wgmma.mma_async.sync.aligned.m64n64k16.f32.bf16.bf16 " REGS32 ", da, %33, 1, 1, 1, 0, 1;\n}\n"
               : ACC8(d, 0), ACC8(d, 8), ACC8(d, 16), ACC8(d, 24)
               : "r"(da_lo), "l"(db), "n"(OFF), "n"(HI));
}
__device__ __forceinline__ void wgmma_rs24(float (&d)[12], const uint32_t (&a)[4], uint64_t db, int acc) {
  asm volatile("{\n.reg .pred p;\nsetp.ne.b32 p, %17, 0;\n"
               "wgmma.mma_async.sync.aligned.m64n24k16.f32.bf16.bf16 {%0,%1,%2,%3,%4,%5,%6,%7,%8,%9,%10,%11}, {%12,%13,%14,%15}, %16, p, 1, 1, 1;\n}\n"
               : ACC8(d, 0), "+f"(d[8]), "+f"(d[9]), "+f"(d[10]), "+f"(d[11])
               : "r"(a[0]), "r"(a[1]), "r"(a[2]), "r"(a[3]), "l"(db), "r"(acc));
}
__device__ __forceinline__ void wgmma_ss40tt(float (&d)[20], uint64_t da, uint64_t db, int acc) {
  asm volatile("{\n.reg .pred p;\nsetp.ne.b32 p, %22, 0;\n"
               "wgmma.mma_async.sync.aligned.m64n40k16.f32.bf16.bf16 {%0,%1,%2,%3,%4,%5,%6,%7,%8,%9,%10,%11,%12,%13,%14,%15,%16,%17,%18,%19}, %20, %21, p, 1, 1, 1, 1;\n}\n"
               : ACC8(d, 0), ACC8(d, 8), "+f"(d[16]), "+f"(d[17]), "+f"(d[18]), "+f"(d[19])
               : "l"(da), "l"(db), "r"(acc));
}
template <uint32_t OFF, uint32_t HI, int ACCUM>
__device__ __forceinline__ void wgmma_ss16(float (&d)[8], uint32_t da_lo, uint64_t db) {
  asm volatile("{\n.reg .b32 lo;\n.reg .b64 da;\n.reg .pred p;\nsetp.ne.b32 p, %12, 0;\nadd.u32 lo, %8, %10;\nmov.b64 da, {lo, %11};\n"
               "wgmma.mma_async.sync.aligned.m64n16k16.f32.bf16.bf16 {%0,%1,%2,%3,%4,%5,%6,%7}, da, %9, p, 1, 1, 0, 1;\n}\n"
               : ACC8(d, 0)
               : "r"(da_lo), "l"(db), "n"(OFF), "n"(HI), "n"(ACCUM));
}
template <int N> __device__ __forceinline__ void pin(float (&d)[N]) {
#pragma unroll
  for (int i = 0; i < N; i++) asm volatile("" : "+f"(d[i])::"memory");
}

__device__ __forceinline__ void pin8(float (&d)[32], const int o) { asm volatile("" : ACC8(d, o)::"memory"); }

template <int I> struct IC { static constexpr int value = I; };
template <int I, int N, class F> __device__ __forceinline__ void static_for(F f) {
  if constexpr (I < N) { f(IC<I>()); static_for<I + 1, N>(f); }
}

struct Params {
  const __nv_bfloat16* x;
  const __nv_bfloat16* wqkv;
  const __nv_bfloat16* wo;
  const __nv_bfloat16* w1;
  const __nv_bfloat16* w3;
  const __nv_bfloat16* w2;
  __nv_bfloat16* out;
};

__global__ void __launch_bounds__(NTHREADS, 1)
fused_block_kernel(const __grid_constant__ CUtensorMap m_qkv, const __grid_constant__ CUtensorMap m_w1,
                   const __grid_constant__ CUtensorMap m_w3, const __grid_constant__ CUtensorMap m_w2,
                   const __grid_constant__ CUtensorMap m_M, const __grid_constant__ CUtensorMap m_x,
                   const __grid_constant__ CUtensorMap m_l, const Params p) {
  extern __shared__ __align__(1024) uint8_t smem_raw[];
  constexpr uint32_t sb = 1024;
  if ((uint32_t)__cvta_generic_to_shared(smem_raw) != sb) __trap();
  const int tid = threadIdx.x, warp = __shfl_sync(0xffffffffu, tid >> 5, 0), lane = tid & 31;
  const int r = blockIdx.x >> 3, j = blockIdx.x & 7;

  GT(0); TSC(0);
  if (tid < 16 * XPF) asm volatile("prefetch.global.L2 [%0];\n" ::"l"(p.x + (size_t)(blockIdx.x * 16 + (tid & 15)) * D_ + (tid >> 4) * 64));
  const int cmain = 72 * j + 8 * (j & 1);
  if (__builtin_expect(warp >= 8, 1)) {
    asm volatile("setmaxnreg.dec.sync.aligned.u32 24;\n");
    if (__builtin_expect(warp == 8, 1)) {
      if (elect_one()) {
#pragma unroll
        for (int b = 0; b < 9; b++) mbar_init(sb + B_X + 8 * b, 1);
        asm volatile("fence.mbarrier_init.release.cluster;\n" ::: "memory");
        mbar_expect(sb + B_X, 16384);
        tma2d(sb + HB, &m_x, 0, 128 * r, sb + B_X);
      }
      __syncwarp();
      asm volatile("bar.arrive 0, 384;\n" ::: "memory");
      TS(2, 20);
      if (elect_one()) {
#pragma unroll
        for (int b = 1; b < 9; b++) {
          mbar_expect(sb + B_X + 8 * b, 16384);
          tma2d(sb + HB + b * 16384, &m_x, 64 * b, 128 * r, sb + B_X + 8 * b);
        }
      }
      __syncwarp();
      TS(2, 21);
      asm volatile("bar.sync 4, 64;\n" ::: "memory");
      if (elect_one()) {
#pragma unroll
        for (int s = 0; s < 6; s++) {
          if (s == WDELAY) mbar_wait(sb + B_X + 8 * XWAIT, 0);
          mbar_expect(sb + B_FULL + 8 * s, SLOT);
          tma2d(sb + s * SLOT, &m_qkv, D_ + cmain, 96 * s, sb + B_FULL + 8 * s);
        }
        const CUtensorMap* mpf = (r & 1) ? &m_w3 : &m_w1;
        if (r < 6) tma2d_prefetch(&m_qkv, 2 * D_ + cmain, 96 * r);
        if (r < 12) { tma2d_prefetch(mpf, 576 * j, 96 * (r >> 1)); tma2d_prefetch(mpf, 576 * j + 32, 96 * (r >> 1)); }
#pragma unroll
        for (int s = 0; s < 6; s++) {
          mbar_wait(sb + B_EMPTY + 8 * s, 0);
          mbar_expect(sb + B_FULL + 8 * s, SLOT);
          tma2d(sb + s * SLOT, &m_qkv, 2 * D_ + cmain, 96 * s, sb + B_FULL + 8 * s);
        }
#pragma unroll 1
        for (int n = 0; n < 18; n++) {
          const int col = 576 * j + 32 * n;
          if (n < 16) { if (r < 12) tma2d_prefetch(mpf, col + 64, 96 * (r >> 1)); }
          else if (r < 6) {
            if (n == 16) tma2d_prefetch(&m_qkv, cmain, 96 * r);
            else tma2d_prefetch(&m_w2, 512, 576 * j + 96 * r);
          }
#pragma unroll
          for (int s = 0; s < 6; s++) {
            mbar_wait(sb + B_EMPTY + 8 * s, (n & 1) ^ 1);
            mbar_expect(sb + B_FULL + 8 * s, SLOT);
            tma2d(sb + s * SLOT, &m_w1, col, 96 * s, sb + B_FULL + 8 * s);
            tma2d(sb + s * SLOT + SLOT / 2, &m_w3, col, 96 * s, sb + B_FULL + 8 * s);
          }
        }
        if (r < 6) tma2d_prefetch(&m_w2, 64 * ((j + 1) & 7), 576 * j + 96 * r);
#pragma unroll
        for (int s = 0; s < 6; s++) {
          mbar_wait(sb + B_EMPTY + 8 * s, 1);
          mbar_expect(sb + B_FULL + 8 * s, SLOT);
          tma2d(sb + s * SLOT, &m_qkv, cmain, 96 * s, sb + B_FULL + 8 * s);
        }
#pragma unroll 1
        for (int n = 0; n < 9; n++) {
          const int col = n == 0 ? 512 : 64 * ((j + n) & 7);
          if (n < 7 && r < 6) tma2d_prefetch(&m_w2, 64 * ((j + n + 2) & 7), 576 * j + 96 * r);
#pragma unroll
          for (int s = 0; s < 6; s++) {
            mbar_wait(sb + B_EMPTY + 8 * s, n & 1);
            mbar_expect(sb + B_FULL + 8 * s, SLOT);
            tma2d(sb + s * SLOT, &m_w2, col, 576 * j + 96 * s, sb + B_FULL + 8 * s);
          }
          if (n == 0) {
            mbar_wait(sb + B_HFREE, 0);
            mbar_wait(sb + B_MRDY, 0);
            asm volatile("fence.proxy.async;\n" ::: "memory");
          }
          mbar_wait(sb + B_EMPTY + 48, (n & 1) ^ 1);
          mbar_expect(sb + B_FULL + 48, 80 * 128);
          tma2d(sb + WO_SLOT, &m_M, col, 80 * j, sb + B_FULL + 48);
          if (n == 4) {
            mbar_expect(sb + B_X, 16384);
            tma2d(sb + XT, &m_x, 64 * j, 128 * r, sb + B_X);
          }
        }
      }
    } else {
      const int ht = tid - 288;
      if (warp == 9) {
        if (elect_one()) {
          asm volatile("prefetch.tensormap [%0];\n" ::"l"(&m_qkv) : "memory");
#pragma unroll
          for (int i = 9; i < 29; i++) mbar_init(sb + BARS + 8 * i, i < 16 ? 1 : i < 26 ? 8 : i == 26 ? 4 : 96);
          asm volatile("fence.mbarrier_init.release.cluster;\n" ::: "memory");
        }
        __syncwarp();
        asm volatile("bar.arrive 4, 64;\n" ::: "memory");
      }
      asm volatile("bar.sync 0, 384;\n" ::: "memory");
      const uint32_t ep = g_epoch[blockIdx.x] + 1;
      mbar_wait(sb + B_X + 8 * 8, 0);
      if (ht < 90) {
        const int e = ht / 18, c = ht - e * 18;
        const __nv_bfloat16* w = p.wo + (size_t)(72 * j + 18 * (r >> 2) + e) * D_ + 144 * (r & 3) + c * 8;
#pragma unroll
        for (int i = 0; i < 4; i++)
          if (i < 3 || ht < 54) cp_async16(sb + WOB + ht * 16 + i * 90 * 16, w + i * 5 * D_);
      }
      mbar_wait(sb + B_XDONE, 0);
      if (warp == 11 && elect_one()) {
        asm volatile("mbarrier.expect_tx.shared::cta.b64 [%0], %1;\n" ::"r"(sb + B_LFULL), "r"(27648) : "memory");
        const int cl = 72 * j + ((j & 1) ? 0 : 64);
#pragma unroll
        for (int m = 0; m < 3; m++)
#pragma unroll
          for (int g = 0; g < 3; g++) tma2d(sb + L24_T + g * 9216 + m * 3072, &m_l, cl + (g == 2 ? 0 : (g + 1) * D_), 192 * m, sb + B_LFULL);
      }
      if (ht < 64) {
#pragma unroll
        for (int i = 0; i < 4; i++) sts128(sb + V_T - 2048 + (i >> 1) * 20480 + (i & 1) * 1024 + ht * 16, 0x3F803F80u, 0x3F803F80u, 0x3F803F80u, 0x3F803F80u);
      }
      asm volatile("cp.async.wait_all;\n" ::: "memory");
      fence_async_smem();
      mbar_arrive(sb + B_LFULL);
      if (warp == 9) TS(3, 1);

      if (ht == 0) {
        mbar_wait(sb + B_KVD, 0);
        red_rel(&g_cnt1[j * 32]);
        wait_ge(&g_cnt1[j * 32], 16 * ep);
      }
      bar_sync(3, 96);
      if (warp == 9) TS(3, 4);
#pragma unroll 1
      for (int i = ht; i < 171; i += 96) {
        const int dp = i / 19, el = i - dp * 19, hd = r >> 2, w = hd >> 1;
        const int d = 18 * hd + 2 * dp - 32 * w;
        const int m = el == 18 ? 56 * w : 18 * hd + el + 8 - 24 * w;
        const float2* src = reinterpret_cast<const float2*>(g_kvp + j * 16 * 1280 + ((w * 4 + (m >> 4)) * 5 + (d >> 3)) * 32 + (m & 7) * 4 + ((d & 7) >> 1)) + ((m >> 3) & 1);
        float s0 = 0.f, s1 = 0.f;
#pragma unroll 1
        for (int r4 = 0; r4 < 4; r4++) {
          const float2 v0 = __ldcg(src), v1 = __ldcg(src + 2560), v2 = __ldcg(src + 2 * 2560), v3 = __ldcg(src + 3 * 2560);
          s0 += (v0.x + v1.x) + (v2.x + v3.x);
          s1 += (v0.y + v1.y) + (v2.y + v3.y);
          src += 4 * 2560;
        }
        sts64(sb + KVS + dp * 160 + el * 8, __float_as_uint(s0), __float_as_uint(s1));
        if ((r & 3) == 0 && el == 18) *reinterpret_cast<float2*>(g_z + j * 72 + hd * 18 + dp * 2) = make_float2(s0, s1);
      }
      bar_sync(3, 96);
      if (warp == 9) TS(3, 5);
#pragma unroll 1
      for (int t = ht; t < 648; t += 96) {
        const int dp = t / 72, cp = t - dp * 72;
        float c0 = 0.f, c1 = 0.f, c2 = 0.f, c3 = 0.f;
        const uint32_t ka = sb + KVS + dp * 160, wa = sb + WOB + cp * 4;
#pragma unroll
        for (int e2 = 0; e2 < 9; e2++) {
          uint32_t a0, a1, a2, a3;
          lds128(a0, a1, a2, a3, ka + e2 * 16);
          const uint32_t w0 = lds32(wa + e2 * 576), w1 = lds32(wa + e2 * 576 + 288);
          c0 = fmaf(__uint_as_float(a0), blo(w0), c0); c1 = fmaf(__uint_as_float(a0), bhi(w0), c1);
          c2 = fmaf(__uint_as_float(a1), blo(w0), c2); c3 = fmaf(__uint_as_float(a1), bhi(w0), c3);
          c0 = fmaf(__uint_as_float(a2), blo(w1), c0); c1 = fmaf(__uint_as_float(a2), bhi(w1), c1);
          c2 = fmaf(__uint_as_float(a3), blo(w1), c2); c3 = fmaf(__uint_as_float(a3), bhi(w1), c3);
        }
        const int d = 18 * (r >> 2) + 2 * dp;
        uint32_t* dst = reinterpret_cast<uint32_t*>(g_M) + (80 * j + ((j & 1) ? (d < 8 ? d + 64 : d - 8) : d)) * 288 + 72 * (r & 3) + cp;
        dst[0] = pack2(c0, c1);
        dst[288] = pack2(c2, c3);
      }
      asm volatile("fence.proxy.async;\n" ::: "memory");
      bar_sync(3, 96);
      if (warp == 9) TS(3, 6);
      if (ht == 0) { red_rel(&g_cnt2[j * 32]); wait_ge(&g_cnt2[j * 32], 16 * ep); }
      bar_sync(3, 96);
      if (ht < 80) {
        const int d = (j & 1) ? (ht < 64 ? ht + 8 : ht - 64) : ht;
        uint32_t zb = 0;
        if (ht < 72) zb = pack2(__ldcg(g_z + j * 72 + d), 0.f);
        const int hd = d / 18;
        const uint32_t w = (hd & 1) ? zb << 16 : zb;
        const uint32_t w0 = hd < 2 ? w : 0u, w1 = hd < 2 ? 0u : w;
        sts128(sb + ZM + ht * 16, w0, w0, w0, w0);
        sts128(sb + ZM + 1280 + ht * 16, w1, w1, w1, w1);
      }
      const uint32_t tag = (ep & 1) << 16;
      if (ht == 95) { sts32(sb + TAGW, tag); g_epoch[blockIdx.x] = ep; }
      fence_async_smem();
      mbar_arrive(sb + B_MRDY);
      if (warp == 9) TS(3, 7);
      if (warp < 11) {
        mbar_wait(sb + B_FULL + 48, 0);
#pragma unroll 1
        for (int i = warp - 9; i < 4; i += 2) {
          const uint4* src = g_part + (size_t)((r * 9 + 8) * 8) * 1024 + j * 128 + i * 32 + lane;
          const int off = ((r * 128 + j * 16 + (lane >> 2)) * D_ + 512 + 16 * i + 2 * (lane & 3)) >> 1;
          float s0, s1, s2, s3, s4, s5, s6, s7;
          {
            const uint32_t* xp = reinterpret_cast<const uint32_t*>(p.x) + off;
            const uint32_t x0 = __ldg(xp), x1 = __ldg(xp + 4 * D_), x2 = __ldg(xp + 4), x3 = __ldg(xp + 4 * D_ + 4);
            s0 = blo(x0); s1 = bhi(x0); s2 = blo(x1); s3 = bhi(x1); s4 = blo(x2); s5 = bhi(x2); s6 = blo(x3); s7 = bhi(x3);
          }
          uint32_t n = 0;
#pragma unroll 1
          for (int jj = 0; jj < 8;) {
            uint32_t v0, v1, v2, v3;
            ld_b128(v0, v1, v2, v3, src);
            if (__all_sync(0xffffffffu, ((v0 ^ tag) & 0x10000u) == 0)) {
              s0 += blo(v0); s1 += __uint_as_float(v0 & 0xfffe0000u); s2 += blo(v1); s3 += bhi(v1);
              s4 += blo(v2); s5 += bhi(v2); s6 += blo(v3); s7 += bhi(v3);
              jj++;
              src += 1024;
            } else {
              __nanosleep(200);
              if (++n > SPIN_LIMIT) __trap();
            }
          }
          uint32_t* op = reinterpret_cast<uint32_t*>(p.out) + off;
          op[0] = pack2(s0, s1); op[4 * D_] = pack2(s2, s3); op[4] = pack2(s4, s5); op[4 * D_ + 4] = pack2(s6, s7);
        }
        if (warp == 9) TS(3, 10);
      }
    }
  } else {
    asm volatile("setmaxnreg.inc.sync.aligned.u32 240;\n");
    asm volatile("bar.sync 0, 384;\n" ::: "memory");
    const int wg = warp >> 2;
    uint32_t a[36][4];
    float dA[32], dB[32];
    const bool l0 = lane == 0;
    constexpr uint64_t dsw128 = mkdesc(sb, 16, 1024, 1);
    constexpr uint64_t dsw64 = mkdesc(sb, SLOT / 2, 512, 2);

    auto issue = [&](float (&d)[32], const uint64_t dbase, const int kstride, const int s, const uint32_t ph, const int init = 0) {
      mbar_wait(sb + B_FULL + 8 * s, ph);
      wg_fence();
#pragma unroll
      for (int ks = 0; ks < 6; ks++) wgmma_rs64(d, a[s * 6 + ks], dbase + ((s * SLOT + ks * kstride) >> 4), (s | ks | init) != 0);
    };
    auto finish = [&](const int rel) {
      wg_commit();
      wg_wait<1>();
      if (rel >= 0 && l0) mbar_arrive(sb + B_EMPTY + 8 * rel);
    };
    auto stW = [&](float (&d)[32], const int s, const uint32_t ph, const int rel) { issue(d, dsw128, 2048, s, ph); finish(rel); };
    auto stF = [&](float (&d)[32], const int s, const uint32_t ph, const int rel) { issue(d, dsw64, 1024, s, ph); finish(rel); };

    TSC(1);
    uint32_t mb0, mb1;
    float r0, r1;
    auto center = [&](const int g) {
#pragma unroll
      for (int ks = 6 * g; ks < 6 * g + 6; ks++) {
        a[ks][0] = bsub2(a[ks][0], mb0); a[ks][1] = bsub2(a[ks][1], mb1);
        a[ks][2] = bsub2(a[ks][2], mb0); a[ks][3] = bsub2(a[ks][3], mb1);
        asm volatile("" : "+r"(a[ks][0]), "+r"(a[ks][1]), "+r"(a[ks][2]), "+r"(a[ks][3])::"memory");
      }
    };
    {
      const uint32_t xa = sb + HB + (warp * 16 + (lane & 15)) * 128;
      const uint32_t sw = lane & 7, hi = lane >> 4;
      constexpr uint32_t ONES = 0x3F803F80u;
      float cs[2][4], cq[2][4];
#pragma unroll
      for (int i = 0; i < 4; i++) { cs[0][i] = cs[1][i] = cq[0][i] = cq[1][i] = 0.f; }
      auto rsum = [&](const int ks) { mma16816(cs[ks & 1], a[ks][0], a[ks][1], a[ks][2], a[ks][3], ONES, ONES); };
      auto rsq = [&](const int ks) {
        mma16816(cq[ks & 1], bmul2(a[ks][0], a[ks][0]), bmul2(a[ks][1], a[ks][1]), bmul2(a[ks][2], a[ks][2]), bmul2(a[ks][3], a[ks][3]), ONES, ONES);
      };
#pragma unroll
      for (int b = 0; b < 9; b++) {
        mbar_wait(sb + B_X + 8 * b, 0);
        if (b == 0 || b == 8) TSC(32 + b);
#pragma unroll
        for (int kk = 0; kk < 4; kk++) ldsm4(a[4 * b + kk][0], a[4 * b + kk][1], a[4 * b + kk][2], a[4 * b + kk][3], xa + b * 16384 + (((2 * kk + hi) ^ sw) << 4));
        if (b > 0) {
#pragma unroll
          for (int ks = 4 * b - 4; ks < 4 * b; ks++) { rsum(ks); rsq(ks); }
        }
      }
#pragma unroll
      for (int ks = 32; ks < 36; ks++) rsum(ks);
#pragma unroll
      for (int ks = 32; ks < 36; ks++) rsq(ks);
      TSC(2);
      const float m0 = (cs[0][0] + cs[1][0]) * (1.f / 576.f), m1 = (cs[0][2] + cs[1][2]) * (1.f / 576.f);
      mb0 = pack2(m0, m0);
      mb1 = pack2(m1, m1);
      center(0);
      TSC(3);
      stW(dA, 0, 0, -1);
      center(1);
      stW(dA, 1, 0, 0);
      const float q0 = (cq[0][0] + cq[1][0]) * (1.f / 576.f), q1 = (cq[0][2] + cq[1][2]) * (1.f / 576.f);
      float v0 = q0 - m0 * m0, v1 = q1 - m1 * m1;
      if (__any_sync(0xffffffffu, v0 < q0 * 0.5f || v1 < q1 * 0.5f)) {
        float s0 = 0.f, s1 = 0.f;
#pragma unroll 1
        for (int ks = 0; ks < 36; ks++) {
          uint32_t e0, e1, e2, e3;
          ldsm4(e0, e1, e2, e3, xa + (ks >> 2) * 16384 + (((2 * (ks & 3) + hi) ^ sw) << 4));
          float t;
          t = blo(e0) - m0; s0 = fmaf(t, t, s0); t = bhi(e0) - m0; s0 = fmaf(t, t, s0);
          t = blo(e2) - m0; s0 = fmaf(t, t, s0); t = bhi(e2) - m0; s0 = fmaf(t, t, s0);
          t = blo(e1) - m1; s1 = fmaf(t, t, s1); t = bhi(e1) - m1; s1 = fmaf(t, t, s1);
          t = blo(e3) - m1; s1 = fmaf(t, t, s1); t = bhi(e3) - m1; s1 = fmaf(t, t, s1);
        }
        s0 += __shfl_xor_sync(0xffffffffu, s0, 1); s1 += __shfl_xor_sync(0xffffffffu, s1, 1);
        s0 += __shfl_xor_sync(0xffffffffu, s0, 2); s1 += __shfl_xor_sync(0xffffffffu, s1, 2);
        v0 = s0 * (1.f / 576.f); v1 = s1 * (1.f / 576.f);
      }
      __syncwarp();
      if (l0) mbar_arrive(sb + B_XDONE);
      r0 = rcp(rbf(sqrta(rbf(rbf(fmaxf(v0, 0.f)) + 1e-5f))));
      r1 = rcp(rbf(sqrta(rbf(rbf(fmaxf(v1, 0.f)) + 1e-5f))));
    }
#pragma unroll
    for (int s = 2; s < 6; s++) {
      center(s);
      stW(dA, s, 0, s - 1);
    }
    TSC(4); GT(1);
    constexpr float LOG2E = 1.4426950408889634f;
    float l0e = r0 * LOG2E, l1e = r1 * LOG2E;
    const uint32_t tile_off = ((lane >> 4) + (j & 1)) * 2048 + (warp * 16 + (lane & 15)) * 16;
    mbar_wait(sb + B_XDONE, 0);
#pragma unroll
    for (int s = 0; s < 6; s++) {
      stW(dB, s, 1, (s + 5) % 6);
      TSC(50 + s);
      if (s < 4) {
        const int t = 2 * s;
        pin8(dA, 4 * t);
        stsm4(sb + PK_T + tile_off + t * 2048, pack2(phi(dA[4 * t], r0, l0e), phi(dA[4 * t + 1], r0, l0e)), pack2(phi(dA[4 * t + 2], r1, l1e), phi(dA[4 * t + 3], r1, l1e)),
              pack2(phi(dA[4 * t + 4], r0, l0e), phi(dA[4 * t + 5], r0, l0e)), pack2(phi(dA[4 * t + 6], r1, l1e), phi(dA[4 * t + 7], r1, l1e)));
      }
    }
    TSC(5);
    {
#pragma unroll
      for (int s = 0; s < 2; s++) {
        stF(dA, s, 0, (s + 5) % 6);
#pragma unroll
        for (int t = 4 * s; t < 4 * s + 4; t += 2) {
          pin8(dB, 4 * t);
          stsm4(sb + V_T + tile_off + t * 2048, pack2(dB[4 * t] * r0, dB[4 * t + 1] * r0), pack2(dB[4 * t + 2] * r1, dB[4 * t + 3] * r1),
                pack2(dB[4 * t + 4] * r0, dB[4 * t + 5] * r0), pack2(dB[4 * t + 6] * r1, dB[4 * t + 7] * r1));
        }
      }
      float dL[12];
      constexpr uint64_t dl = mkdesc(sb + L24_T, 128, 576 * 16, 0);
      mbar_wait(sb + B_LFULL, 0);
#pragma unroll
      for (int s = 2; s < 5; s++) {
        mbar_wait(sb + B_FULL + 8 * s, 0);
        wg_fence();
#pragma unroll
        for (int ks = 12 * (s - 2); ks < 12 * (s - 1); ks++) wgmma_rs24(dL, a[ks], dl + ks * 16, ks != 0);
#pragma unroll
        for (int ks = 0; ks < 6; ks++) wgmma_rs64(dA, a[s * 6 + ks], dsw64 + ((s * SLOT + ks * 1024) >> 4), 1);
        finish(s - 1);
      }
      stF(dA, 5, 0, 4);
      pin(dL);
      const uint32_t lo = ((j & 1) ? 0 : 8 * 2048) + warp * 256 + lane * 4;
      sts32(sb + PK_T + lo, pack2(phi(dL[0], r0, l0e), phi(dL[1], r0, l0e)));
      sts32(sb + PK_T + lo + 128, pack2(phi(dL[2], r1, l1e), phi(dL[3], r1, l1e)));
      sts32(sb + V_T + lo, pack2(dL[4] * r0, dL[5] * r0));
      sts32(sb + V_T + lo + 128, pack2(dL[6] * r1, dL[7] * r1));
      sts64(sb + Q8 + tid * 8, pack2(dL[8], dL[9]), pack2(dL[10], dL[11]));
      fence_async_smem();
      __syncwarp();
      if (l0) mbar_arrive(sb + B_KVT);
    }
    TSC(6);
    uint32_t hs = sb + HB + wg * HHALF + (tid & 127) * 16;
    uint32_t hp0, hp1;
    const float iq0 = rcp(r0 * r0), iq1 = rcp(r1 * r1);
    auto epiF = [&](float (&d)[32], const int pc) {
      asm volatile("" : "+f"(d[4 * pc]), "+f"(d[4 * pc + 1]), "+f"(d[4 * pc + 2]), "+f"(d[4 * pc + 3]), "+f"(d[4 * pc + 16]), "+f"(d[4 * pc + 17]),
                   "+f"(d[4 * pc + 18]), "+f"(d[4 * pc + 19])::"memory");
      const float g0 = d[4 * pc], g1 = d[4 * pc + 1], g2 = d[4 * pc + 2], g3 = d[4 * pc + 3];
      const uint32_t h0 = pack2(g0 * d[4 * pc + 16] * rcp(fmaf(ex2(-g0 * l0e), iq0, iq0)), g1 * d[4 * pc + 17] * rcp(fmaf(ex2(-g1 * l0e), iq0, iq0)));
      const uint32_t h1 = pack2(g2 * d[4 * pc + 18] * rcp(fmaf(ex2(-g2 * l1e), iq1, iq1)), g3 * d[4 * pc + 19] * rcp(fmaf(ex2(-g3 * l1e), iq1, iq1)));
      if (pc & 1) {
        sts128(hs, hp0, hp1, h0, h1);
        hs += 2048;
      } else {
        hp0 = h0; hp1 = h1;
        asm volatile("" : "+r"(hp0), "+r"(hp1)::"memory");
      }
    };
    {
      stF(dB, 0, 1, 5);
      epiF(dA, 0); epiF(dA, 1);
      stF(dB, 1, 1, 0);
      epiF(dA, 2); epiF(dA, 3);
      float dK[20];
      const uint64_t ka = mkdesc(sb + V_T - 2048 + wg * 3 * 2048, 128, 2048, 0), kb = mkdesc(sb + PK_T + wg * 4 * 2048, 128, 2048, 0);
      mbar_wait(sb + B_KVT, 0);
      mbar_wait(sb + B_FULL + 8 * 2, 1);
      wg_fence();
#pragma unroll
      for (int ks = 0; ks < 8; ks++) wgmma_ss40tt(dK, ka + ks * 16, kb + ks * 16, ks != 0);
#pragma unroll
      for (int ks = 0; ks < 6; ks++) wgmma_rs64(dB, a[12 + ks], dsw64 + ((2 * SLOT + ks * 1024) >> 4), 1);
      finish(1);
      stF(dB, 3, 1, 2);
      pin(dK);
      float4* dst = g_kvp + (j * 16 + r) * 1280 + warp * 160 + lane;
#pragma unroll
      for (int t = 0; t < 5; t++) __stcg(dst + t * 32, make_float4(dK[4 * t], dK[4 * t + 1], dK[4 * t + 2], dK[4 * t + 3]));
      __syncwarp();
      if (l0) mbar_arrive(sb + B_KVD);
      stF(dB, 4, 1, 3);
    }
#pragma unroll 1
    for (int it = 0; it < 8; it++) {
      stF(dB, 5, 1, 4);
      stF(dA, 0, 0, 5);
#pragma unroll
      for (int s = 1; s < 5; s++) { epiF(dB, s - 1); stF(dA, s, 0, s - 1); }
      stF(dA, 5, 0, 4);
      stF(dB, 0, 1, 5);
#pragma unroll
      for (int s = 1; s < 5; s++) { epiF(dA, s - 1); stF(dB, s, 1, s - 1); }
      TSC(7 + it);
    }
    stF(dB, 5, 1, 4);
    TSC(15);
    const uint32_t hl = sb + HB + wg * HHALF + (tid & 127) * 16;
    auto reload = [&](auto k0, auto k1) {
      static_for<decltype(k0)::value, decltype(k1)::value>([&](auto k) { lds128_inplace<decltype(k)::value * 2048>(a[decltype(k)::value], hl); });
    };
    stW(dA, 0, 0, 5);
    epiF(dB, 0);
    stW(dA, 1, 0, 0);
    reload(IC<0>(), IC<4>());
    epiF(dB, 1);
    stW(dA, 2, 0, 1);
    reload(IC<4>(), IC<8>());
    epiF(dB, 2);
    stW(dA, 3, 0, 2);
    reload(IC<8>(), IC<12>());
    __syncwarp();
    if (l0 && wg == 0) mbar_arrive(sb + B_HFREE);
    epiF(dB, 3);
    stW(dA, 4, 0, 3);
    reload(IC<12>(), IC<17>());
    stW(dA, 5, 0, 4);
    reload(IC<17>(), IC<22>());
    const uint32_t ot = sb + HB + wg * HHALF;
    const uint32_t do_a = (uint32_t)mkdesc(ot, 128, 1280, 0);
    constexpr uint64_t do_b = mkdesc(sb + WO_SLOT, 16, 1024, 1);
    auto stO = [&](float (&d)[32], const uint32_t ph, const int rel) {
      mbar_wait(sb + B_FULL + 48, ph);
      wg_fence();
      wgmma_ss64<0, 80>(d, do_a, do_b);
      wgmma_ss64<16, 80>(d, do_a, do_b + 128);
      wgmma_ss64<32, 80>(d, do_a, do_b + 256);
      wgmma_ss64<48, 80>(d, do_a, do_b + 384);
      wgmma_ss64<64, 80>(d, do_a, do_b + 512);
      finish(rel);
    };
    uint32_t tag;
    auto epiP = [&](float (&d)[32], const int step) {
      pin(d);
      const int c = step == 0 ? 8 : ((j + step) & 7);
      uint4* dst = g_part + (size_t)((r * 9 + c) * 8 + j) * 1024 + warp * 128 + lane;
#pragma unroll
      for (int i = 0; i < 4; i++)
        st_b128(dst + i * 32, (pack2(d[8 * i], d[8 * i + 1]) & 0xfffeffffu) | tag, pack2(d[8 * i + 2], d[8 * i + 3]), pack2(d[8 * i + 4], d[8 * i + 5]), pack2(d[8 * i + 6], d[8 * i + 7]));
    };
    TSC(16);
    {
      stW(dB, 0, 1, 5);
      reload(IC<22>(), IC<26>());
      asm volatile("" : "+f"(l0e), "+f"(l1e));
      r0 = l0e * (1.f / LOG2E); r1 = l1e * (1.f / LOG2E);
      uint32_t pq[18];
      const uint32_t oa = ot + ((warp & 3) * 2 + ((lane >> 3) & 1)) * 1280 + (lane >> 4) * 128 + (lane & 7) * 16;
      auto phiq = [&](const int t0, const int t1) {
#pragma unroll
        for (int t = t0; t < t1; t++) {
          asm volatile("" : "+f"(dA[4 * t]), "+f"(dA[4 * t + 1]), "+f"(dA[4 * t + 2]), "+f"(dA[4 * t + 3])::"memory");
          pq[2 * t] = pack2(phi(dA[4 * t], r0, l0e), phi(dA[4 * t + 1], r0, l0e));
          pq[2 * t + 1] = pack2(phi(dA[4 * t + 2], r1, l1e), phi(dA[4 * t + 3], r1, l1e));
          asm volatile("" : "+r"(pq[2 * t]), "+r"(pq[2 * t + 1])::"memory");
        }
      };
      phiq(0, 3);
      bar_sync(1 + wg, 128);
      stW(dB, 1, 1, 0);
      reload(IC<26>(), IC<30>());
      phiq(3, 6);
      stW(dB, 2, 1, 1);
      phiq(6, 8);
      {
        uint32_t q0, q1;
        lds64(q0, q1, sb + Q8 + tid * 8);
        pq[16] = pack2(phi(blo(q0), r0, l0e), phi(bhi(q0), r0, l0e));
        pq[17] = pack2(phi(blo(q1), r1, l1e), phi(bhi(q1), r1, l1e));
      }
#pragma unroll
      for (int t = 0; t < 8; t += 2) stsm4(oa + t * 128, pq[2 * t], pq[2 * t + 1], pq[2 * t + 2], pq[2 * t + 3]);
      stsm4(oa + 1024, pq[16], pq[17], 0u, 0u);
      fence_async_smem();
      TSC(17);
      mbar_wait(sb + B_MRDY, 0);
      TSC(18);
      tag = lds32(sb + TAGW);
      float den[8];
      constexpr uint64_t dz = mkdesc(sb + ZM, 128, 1280, 0);
      bar_sync(1 + wg, 128);
      issue(dB, dsw128, 2048, 3, 1);
      wgmma_ss16<0, 80, 0>(den, do_a, dz);
      wgmma_ss16<16, 80, 1>(den, do_a, dz + 16);
      wgmma_ss16<32, 80, 1>(den, do_a, dz + 32);
      wgmma_ss16<48, 80, 1>(den, do_a, dz + 48);
      wgmma_ss16<64, 80, 1>(den, do_a, dz + 64);
      finish(2);
      reload(IC<30>(), IC<36>());
      stW(dB, 4, 1, 3);
      pin(den);
      uint32_t iv[8];
#pragma unroll
      for (int i = 0; i < 8; i++) { const float t = rcp(den[i] + 1e-6f); iv[i] = pack2(t, t); }
      const int u = 2 * (lane & 3) + 8 * (j & 1);
#pragma unroll
      for (int t = 0; t < 10; t += 2) {
        uint32_t o[4];
#pragma unroll
        for (int z = 0; z < 2; z++) {
          const int tt = t + z;
          if (tt < 9) {
            const int lo = tt == 0 ? 0 : tt >= 7 ? 3 : (tt - 1) >> 1, hi = tt == 8 ? 0 : (tt == 0 || tt == 7) ? lo : lo + 1;
            const bool up = tt == 8 ? (j & 1) : 8 * tt + u >= 18 * hi;
            const int il = (lo >> 1) * 4 + (lo & 1), ih = (hi >> 1) * 4 + (hi & 1);
            o[2 * z] = bmul2(pq[2 * tt], up ? iv[ih] : iv[il]);
            o[2 * z + 1] = bmul2(pq[2 * tt + 1], up ? iv[ih + 2] : iv[il + 2]);
          } else {
            o[2 * z] = 0; o[2 * z + 1] = 0;
          }
        }
        stsm4(oa + t * 128, o[0], o[1], o[2], o[3]);
      }
      fence_async_smem();
      stW(dB, 5, 1, 4);
      bar_sync(1 + wg, 128);
      stO(dB, 0, 5);
    }
    stW(dA, 0, 0, 6);
    epiP(dB, 0);
    TSC(19);
    auto ldp = [&](uint32_t (&v)[16], const int c, const int dj) {
      const uint4* src = g_part + (size_t)((r * 9 + c) * 8 + ((j + dj) & 7)) * 1024 + warp * 128 + lane;
#pragma unroll
      for (int i = 0; i < 4; i++) ld_b128(v[4 * i], v[4 * i + 1], v[4 * i + 2], v[4 * i + 3], src + i * 32);
    };
    auto chk = [&](uint32_t (&v)[16], const int c, const int dj) {
      uint32_t n = 0;
      while (__any_sync(0xffffffffu, (((v[0] ^ tag) | (v[4] ^ tag) | (v[8] ^ tag) | (v[12] ^ tag)) & 0x10000u) != 0)) {
        ldp(v, c, dj);
        if (++n > SPIN_LIMIT) asm volatile("trap;");
      }
    };
    auto unp = [&](float (&d)[32], uint32_t (&v)[16], const int i) {
      d[8 * i] = blo(v[4 * i]); d[8 * i + 1] = __uint_as_float(v[4 * i] & 0xfffe0000u); d[8 * i + 2] = blo(v[4 * i + 1]); d[8 * i + 3] = bhi(v[4 * i + 1]);
      d[8 * i + 4] = blo(v[4 * i + 2]); d[8 * i + 5] = bhi(v[4 * i + 2]); d[8 * i + 6] = blo(v[4 * i + 3]); d[8 * i + 7] = bhi(v[4 * i + 3]);
      pin8(d, 8 * i);
    };
#pragma unroll
    for (int s = 1; s < 6; s++) stW(dA, s, 0, s - 1);
    stO(dA, 1, 5);
    stW(dB, 0, 1, 6);
    epiP(dA, 1);
    TSC(20);
#pragma unroll 1
    for (int it = 0; it < 3; it++) {
      uint32_t v[16];
      stW(dB, 1, 1, 0);
#pragma unroll
      for (int i = 0; i < 16; i++) v[i] = (i & 3) ? 0u : tag;
      if (it > 0) ldp(v, (j + 3 + 2 * it) & 7, 3);
      stW(dB, 2, 1, 1);
      stW(dB, 3, 1, 2);
      stW(dB, 4, 1, 3);
      chk(v, (j + 3 + 2 * it) & 7, 3);
      unp(dA, v, 0); unp(dA, v, 1);
      stW(dB, 5, 1, 4);
      unp(dA, v, 2); unp(dA, v, 3);
      stO(dB, 0, 5);
      issue(dA, dsw128, 2048, 0, 0, 1); finish(6);
      epiP(dB, 2 + 2 * it);
      stW(dA, 1, 0, 0);
      ldp(v, (j + 4 + 2 * it) & 7, 3);
      stW(dA, 2, 0, 1);
      stW(dA, 3, 0, 2);
      stW(dA, 4, 0, 3);
      chk(v, (j + 4 + 2 * it) & 7, 3);
      unp(dB, v, 0); unp(dB, v, 1);
      stW(dA, 5, 0, 4);
      unp(dB, v, 2); unp(dB, v, 3);
      stO(dA, 1, 5);
      issue(dB, dsw128, 2048, 0, 1, 1); finish(6);
      epiP(dA, 3 + 2 * it);
      TSC(21 + it);
    }
    {
      uint32_t v[16], w[16], xv[16];
      float f[32] = {};
      auto addv = [&](uint32_t (&v)[16], const int i) {
        f[8 * i] += blo(v[4 * i]); f[8 * i + 1] += __uint_as_float(v[4 * i] & 0xfffe0000u); f[8 * i + 2] += blo(v[4 * i + 1]); f[8 * i + 3] += bhi(v[4 * i + 1]);
        f[8 * i + 4] += blo(v[4 * i + 2]); f[8 * i + 5] += bhi(v[4 * i + 2]); f[8 * i + 6] += blo(v[4 * i + 3]); f[8 * i + 7] += bhi(v[4 * i + 3]);
        pin8(f, 8 * i);
      };
      stW(dB, 1, 1, -1);
      TSC(44);
      ldp(v, j, 2);
      mbar_wait(sb + B_X, 1);
#pragma unroll
      for (int i = 0; i < 4; i++)
        ldsm4(xv[4 * i], xv[4 * i + 1], xv[4 * i + 2], xv[4 * i + 3], sb + XT + (warp * 16 + (lane & 15)) * 128 + (((2 * i + (lane >> 4)) ^ (lane & 7)) << 4));
      stW(dB, 2, 1, -1);
      TSC(45);
#pragma unroll
      for (int i = 0; i < 16; i++) { f[2 * i] = blo(xv[i]); f[2 * i + 1] = bhi(xv[i]); }
      pin(f);
      stW(dB, 3, 1, -1);
      TSC(46);
      ldp(w, j, 1);
      stW(dB, 4, 1, -1);
      TSC(47);
      chk(v, j, 2);
      TSC(48);
      addv(v, 0); addv(v, 1);
      stW(dB, 5, 1, -1);
      TSC(49);
      addv(v, 2); addv(v, 3);
      stO(dB, 0, -1);
      TSC(24);
      chk(w, j, 1);
      addv(w, 0); addv(w, 1); addv(w, 2); addv(w, 3);
      TSC(25);
      wg_wait<0>();
      TSC(26); GT(2);
      pin(dB);
      const uint32_t ps = sb + HB + wg * HHALF + STG + (warp & 3) * 2048;
      const int row = lane & 15;
#pragma unroll
      for (int t = 0; t < 8; t += 2)
        stsm4(ps + row * 128 + (((t + (lane >> 4)) ^ (row & 7)) << 4),
              pack2(f[4 * t] + dB[4 * t], f[4 * t + 1] + dB[4 * t + 1]), pack2(f[4 * t + 2] + dB[4 * t + 2], f[4 * t + 3] + dB[4 * t + 3]),
              pack2(f[4 * t + 4] + dB[4 * t + 4], f[4 * t + 5] + dB[4 * t + 5]), pack2(f[4 * t + 6] + dB[4 * t + 6], f[4 * t + 7] + dB[4 * t + 7]));
      __syncwarp();
#pragma unroll
      for (int i = 0; i < 4; i++) {
        const int rr = i * 4 + (lane >> 3), ch = lane & 7;
        uint4 o;
        lds128(o.x, o.y, o.z, o.w, ps + rr * 128 + ((ch ^ (rr & 7)) << 4));
        *reinterpret_cast<uint4*>(p.out + (size_t)(r * 128 + warp * 16 + rr) * D_ + 64 * j + ch * 8) = o;
      }
    }
    TSC(27); GT(3);
  }
}

typedef CUresult (*EncodeFn)(CUtensorMap*, CUtensorMapDataType, cuuint32_t, void*, const cuuint64_t*, const cuuint64_t*, const cuuint32_t*,
                             const cuuint32_t*, CUtensorMapInterleave, CUtensorMapSwizzle, CUtensorMapL2promotion, CUtensorMapFloatOOBfill);

CUtensorMap make_map(EncodeFn enc, const void* ptr, int rows, int cols, int brow, int bcol, CUtensorMapSwizzle sw) {
  CUtensorMap m;
  cuuint64_t gd[2] = {(cuuint64_t)cols, (cuuint64_t)rows};
  cuuint64_t gs[1] = {(cuuint64_t)cols * 2};
  cuuint32_t bd[2] = {(cuuint32_t)bcol, (cuuint32_t)brow};
  cuuint32_t es[2] = {1, 1};
  enc(&m, CU_TENSOR_MAP_DATA_TYPE_BFLOAT16, 2, const_cast<void*>(ptr), gd, gs, bd, es, CU_TENSOR_MAP_INTERLEAVE_NONE, sw,
      CU_TENSOR_MAP_L2_PROMOTION_L2_128B, CU_TENSOR_MAP_FLOAT_OOB_FILL_NONE);
  return m;
}

}

extern "C" void kernel_launch(void* const* d_in, const int* in_sizes, int n_in, void* d_out, int out_size) {
  (void)in_sizes; (void)n_in; (void)out_size;
  static EncodeFn enc = nullptr;
  static void* m_ptr = nullptr;
  if (!enc) {
    cudaGetSymbolAddress(&m_ptr, g_M);
    cudaDriverEntryPointQueryResult qr;
    cudaGetDriverEntryPoint("cuTensorMapEncodeTiled", (void**)&enc, cudaEnableDefault, &qr);
    cudaFuncSetAttribute(fused_block_kernel, cudaFuncAttributeMaxDynamicSharedMemorySize, SMEM_BYTES);
  }
  Params p;
  p.x = (const __nv_bfloat16*)d_in[0];
  p.wqkv = (const __nv_bfloat16*)d_in[1];
  p.wo = (const __nv_bfloat16*)d_in[2];
  p.w1 = (const __nv_bfloat16*)d_in[4];
  p.w3 = (const __nv_bfloat16*)d_in[5];
  p.w2 = (const __nv_bfloat16*)d_in[6];
  p.out = (__nv_bfloat16*)d_out;
  const CUtensorMap m_qkv = make_map(enc, p.wqkv, D_, 3 * D_, 96, 64, CU_TENSOR_MAP_SWIZZLE_128B);
  const CUtensorMap m_w1 = make_map(enc, p.w1, D_, F_, 96, 32, CU_TENSOR_MAP_SWIZZLE_64B);
  const CUtensorMap m_w3 = make_map(enc, p.w3, D_, F_, 96, 32, CU_TENSOR_MAP_SWIZZLE_64B);
  const CUtensorMap m_w2 = make_map(enc, p.w2, F_, D_, 96, 64, CU_TENSOR_MAP_SWIZZLE_128B);
  const CUtensorMap m_M = make_map(enc, m_ptr, 8 * 80, D_, 80, 64, CU_TENSOR_MAP_SWIZZLE_128B);
  const CUtensorMap m_x = make_map(enc, p.x, 2048, D_, 128, 64, CU_TENSOR_MAP_SWIZZLE_128B);
  const CUtensorMap m_l = make_map(enc, p.wqkv, D_, 3 * D_, 192, 8, CU_TENSOR_MAP_SWIZZLE_NONE);
  fused_block_kernel<<<128, NTHREADS, SMEM_BYTES>>>(m_qkv, m_w1, m_w3, m_w2, m_M, m_x, m_l, p);
}
```

```cpp
#include <cuda_runtime.h>
#include <cuda.h>
#include <cuda_bf16.h>
#include <stdint.h>

namespace {

constexpr int D_ = 576, F_ = 4608;
constexpr int NTHREADS = 384;

constexpr uint32_t SLOT = 12288;
constexpr uint32_t HB = 6 * SLOT;
constexpr uint32_t HHALF = 73728;
constexpr uint32_t PK_T = HB + 45056;
constexpr uint32_t V_T = HB + HHALF + 18432;
constexpr uint32_t L24_T = HB + 16384;
constexpr uint32_t WO_SLOT = HB + 12288;
constexpr uint32_t XT = HB + 24576;
constexpr uint32_t STG = 49152;
constexpr uint32_t Q8 = HB + 2 * HHALF;
constexpr uint32_t WOB = Q8 + 2048;
constexpr uint32_t KVS = WOB + 5184;
constexpr uint32_t ZM = WOB;
constexpr uint32_t TAGW = KVS + 1440;
constexpr uint32_t BARS = TAGW + 32;
constexpr uint32_t SMEM_BYTES = BARS + 512;

constexpr uint32_t B_X = BARS;
constexpr uint32_t B_FULL = BARS + 8 * 9;
constexpr uint32_t B_EMPTY = BARS + 8 * 16;
constexpr uint32_t B_XDONE = BARS + 8 * 23;
constexpr uint32_t B_KVT = BARS + 8 * 24;
constexpr uint32_t B_KVD = BARS + 8 * 25;
constexpr uint32_t B_HFREE = BARS + 8 * 26;
constexpr uint32_t B_LFULL = BARS + 8 * 27;
constexpr uint32_t B_MRDY = BARS + 8 * 28;

#define XPD 250
#define LTMA 0
#define WDELAY 2
#define XWAIT 8
constexpr uint32_t SPIN_LIMIT = 1u << 22;

__device__ uint4 g_part[16 * 9 * 8 * 1024];
__device__ float4 g_kvp[8 * 16 * 1280];
__device__ __align__(128) __nv_bfloat16 g_M[8 * 80 * 576];
__device__ __align__(16) float g_z[8 * 72];
__device__ uint32_t g_cnt1[8 * 32], g_cnt2[8 * 32];
__device__ uint32_t g_epoch[128];

#define TS(slot, i)
#define TSC(i)
#define GT(i)

__device__ __forceinline__ void wg_fence() { asm volatile("wgmma.fence.sync.aligned;\n" ::: "memory"); }
__device__ __forceinline__ void wg_commit() { asm volatile("wgmma.commit_group.sync.aligned;\n" ::: "memory"); }
template <int N> __device__ __forceinline__ void wg_wait() { asm volatile("wgmma.wait_group.sync.aligned %0;\n" ::"n"(N) : "memory"); }
__host__ __device__ constexpr uint64_t mkdesc(uint32_t addr, uint32_t lbo, uint32_t sbo, uint32_t sw) {
  return (uint64_t)((addr & 0x3FFFF) >> 4) | ((uint64_t)(lbo >> 4) << 16) | ((uint64_t)(sbo >> 4) << 32) | ((uint64_t)sw << 62);
}
__device__ __forceinline__ void mbar_init(uint32_t a, uint32_t c) { asm volatile("mbarrier.init.shared::cta.b64 [%0], %1;\n" ::"r"(a), "r"(c) : "memory"); }
__device__ __forceinline__ void mbar_expect(uint32_t a, uint32_t b) { asm volatile("mbarrier.arrive.expect_tx.shared::cta.b64 _, [%0], %1;\n" ::"r"(a), "r"(b) : "memory"); }
__device__ __forceinline__ void mbar_arrive(uint32_t a) { asm volatile("mbarrier.arrive.shared::cta.b64 _, [%0];\n" ::"r"(a) : "memory"); }
__device__ __forceinline__ void mbar_wait(uint32_t a, uint32_t ph) {
  asm volatile(
      "{\n.reg .pred p;\n.reg .u32 n;\n"
      "mov.u32 n, 0;\n"
      "LOOP:\n"
      "mbarrier.try_wait.parity.shared::cta.b64 p, [%0], %1;\n"
      "@p bra DONE;\n"
      "add.u32 n, n, 1;\n"
      "setp.gt.u32 p, n, %2;\n"
      "@p trap;\n"
      "bra LOOP;\n"
      "DONE:\n}\n" ::"r"(a), "r"(ph), "n"(SPIN_LIMIT) : "memory");
}
__device__ __forceinline__ void cp_async16(uint32_t dst, const void* src) {
  asm volatile("cp.async.cg.shared.global [%0], [%1], 16;\n" ::"r"(dst), "l"(src) : "memory");
}
__device__ __forceinline__ void tma2d(uint32_t dst, const CUtensorMap* m, int c0, int c1, uint32_t bar) {
  asm volatile("cp.async.bulk.tensor.2d.shared::cluster.global.mbarrier::complete_tx::bytes [%0], [%1, {%3, %4}], [%2];\n" ::"r"(dst), "l"(m), "r"(bar), "r"(c0), "r"(c1) : "memory");
}
__device__ __forceinline__ void tma2d_prefetch(const CUtensorMap* m, int c0, int c1) {
  asm volatile("cp.async.bulk.prefetch.tensor.2d.L2.global [%0, {%1, %2}];\n" ::"l"(m), "r"(c0), "r"(c1) : "memory");
}
__device__ __forceinline__ void fence_async_smem() { asm volatile("fence.proxy.async.shared::cta;\n" ::: "memory"); }
__device__ __forceinline__ void bar_sync(int id, int n) { asm volatile("bar.sync %0, %1;\n" ::"r"(id), "r"(n) : "memory"); }
__device__ __forceinline__ void ldsm4(uint32_t& r0, uint32_t& r1, uint32_t& r2, uint32_t& r3, uint32_t a) {
  asm volatile("ldmatrix.sync.aligned.m8n8.x4.shared.b16 {%0,%1,%2,%3}, [%4];\n" : "=r"(r0), "=r"(r1), "=r"(r2), "=r"(r3) : "r"(a) : "memory");
}
__device__ __forceinline__ void stsm4(uint32_t a, uint32_t r0, uint32_t r1, uint32_t r2, uint32_t r3) {
  asm volatile("stmatrix.sync.aligned.m8n8.x4.shared.b16 [%0], {%1,%2,%3,%4};\n" ::"r"(a), "r"(r0), "r"(r1), "r"(r2), "r"(r3) : "memory");
}
__device__ __forceinline__ void sts128(uint32_t a, uint32_t r0, uint32_t r1, uint32_t r2, uint32_t r3) {
  asm volatile("st.shared.v4.b32 [%0], {%1,%2,%3,%4};\n" ::"r"(a), "r"(r0), "r"(r1), "r"(r2), "r"(r3) : "memory");
}
__device__ __forceinline__ void lds128(uint32_t& r0, uint32_t& r1, uint32_t& r2, uint32_t& r3, uint32_t a) {
  asm volatile("ld.shared.v4.b32 {%0,%1,%2,%3}, [%4];\n" : "=r"(r0), "=r"(r1), "=r"(r2), "=r"(r3) : "r"(a) : "memory");
}
template <int OFF>
__device__ __forceinline__ void lds128_inplace(uint32_t (&r)[4], uint32_t a) {
  asm volatile("{\n.reg .pred p;\nsetp.ne.u32 p, %4, 0;\n@p ld.shared.v4.b32 {%0,%1,%2,%3}, [%4 + %5];\n}\n"
               : "+r"(r[0]), "+r"(r[1]), "+r"(r[2]), "+r"(r[3]) : "r"(a), "n"(OFF) : "memory");
}
__device__ __forceinline__ void sts64(uint32_t a, uint32_t r0, uint32_t r1) { asm volatile("st.shared.v2.b32 [%0], {%1,%2};\n" ::"r"(a), "r"(r0), "r"(r1) : "memory"); }
__device__ __forceinline__ void lds64(uint32_t& r0, uint32_t& r1, uint32_t a) { asm volatile("ld.shared.v2.b32 {%0,%1}, [%2];\n" : "=r"(r0), "=r"(r1) : "r"(a) : "memory"); }
__device__ __forceinline__ uint32_t lds32(uint32_t a) { uint32_t v; asm volatile("ld.shared.b32 %0, [%1];\n" : "=r"(v) : "r"(a) : "memory"); return v; }
__device__ __forceinline__ void sts32(uint32_t a, uint32_t r0) { asm volatile("st.shared.b32 [%0], %1;\n" ::"r"(a), "r"(r0) : "memory"); }
__device__ __forceinline__ void mma16816(float (&c)[4], uint32_t a0, uint32_t a1, uint32_t a2, uint32_t a3, uint32_t b0, uint32_t b1) {
  asm volatile("mma.sync.aligned.m16n8k16.row.col.f32.bf16.bf16.f32 {%0,%1,%2,%3}, {%4,%5,%6,%7}, {%8,%9}, {%0,%1,%2,%3};\n"
               : "+f"(c[0]), "+f"(c[1]), "+f"(c[2]), "+f"(c[3]) : "r"(a0), "r"(a1), "r"(a2), "r"(a3), "r"(b0), "r"(b1));
}
__device__ __forceinline__ uint32_t pack2(float lo, float hi) {
  uint32_t r;
  asm("cvt.rn.bf16x2.f32 %0, %1, %2;\n" : "=r"(r) : "f"(hi), "f"(lo));
  return r;
}
__device__ __forceinline__ float blo(uint32_t w) { return __uint_as_float(w << 16); }
__device__ __forceinline__ float bhi(uint32_t w) { return __uint_as_float(w & 0xffff0000u); }
__device__ __forceinline__ float rbf(float x) { return __bfloat162float(__float2bfloat16_rn(x)); }
__device__ __forceinline__ float ex2(float x) { float r; asm("ex2.approx.ftz.f32 %0, %1;\n" : "=f"(r) : "f"(x)); return r; }
__device__ __forceinline__ float rcp(float x) { float r; asm("rcp.approx.ftz.f32 %0, %1;\n" : "=f"(r) : "f"(x)); return r; }
__device__ __forceinline__ float sqrta(float x) { float r; asm("sqrt.approx.ftz.f32 %0, %1;\n" : "=f"(r) : "f"(x)); return r; }
__device__ __forceinline__ uint32_t bsub2(uint32_t a, uint32_t b) { uint32_t r; asm("sub.rn.bf16x2 %0, %1, %2;\n" : "=r"(r) : "r"(a), "r"(b)); return r; }
__device__ __forceinline__ uint32_t ld_acq(const uint32_t* p) { uint32_t v; asm volatile("ld.acquire.gpu.global.u32 %0, [%1];\n" : "=r"(v) : "l"(p) : "memory"); return v; }
__device__ __forceinline__ void st_b128(void* p, uint32_t a, uint32_t b, uint32_t c, uint32_t d) {
  asm volatile("st.relaxed.gpu.global.v4.b32 [%0], {%1, %2, %3, %4};\n" ::"l"(p), "r"(a), "r"(b), "r"(c), "r"(d) : "memory");
}
__device__ __forceinline__ void ld_b128(uint32_t& a, uint32_t& b, uint32_t& c, uint32_t& d, const void* p) {
  asm volatile("{\n.reg .b128 v;\nld.relaxed.gpu.global.b128 v, [%4];\nmov.b128 {%0, %1, %2, %3}, v;\n}\n" : "=r"(a), "=r"(b), "=r"(c), "=r"(d) : "l"(p) : "memory");
}
__device__ __forceinline__ bool elect_one() {
  uint32_t ok;
  asm volatile("{\n.reg .pred p;\nelect.sync _|p, 0xffffffff;\nselp.u32 %0, 1, 0, p;\n}\n" : "=r"(ok));
  return ok;
}
__device__ __forceinline__ uint32_t bmul2(uint32_t a, uint32_t b) { uint32_t r; asm("mul.rn.bf16x2 %0, %1, %2;\n" : "=r"(r) : "r"(a), "r"(b)); return r; }
__device__ __forceinline__ void red_rel(uint32_t* p) { asm volatile("red.release.gpu.global.add.u32 [%0], 1;\n" ::"l"(p) : "memory"); }
__device__ __forceinline__ void wait_ge(const uint32_t* p, uint32_t target) {
  uint32_t n = 0;
  while ((int32_t)(ld_acq(p) - target) < 0) {
    __nanosleep(64);
    if (++n > SPIN_LIMIT) __trap();
  }
}
__device__ __forceinline__ float phi(float a, float r, float rl) { return fmaf(fmaxf(a, 0.f), r, __saturatef(ex2(a * rl) + 1e-6f)); }

#define ACC8(d, o) "+f"(d[o + 0]), "+f"(d[o + 1]), "+f"(d[o + 2]), "+f"(d[o + 3]), "+f"(d[o + 4]), "+f"(d[o + 5]), "+f"(d[o + 6]), "+f"(d[o + 7])
#define REGS32 "{%0,%1,%2,%3,%4,%5,%6,%7,%8,%9,%10,%11,%12,%13,%14,%15,%16,%17,%18,%19,%20,%21,%22,%23,%24,%25,%26,%27,%28,%29,%30,%31}"
__device__ __forceinline__ void wgmma_rs64(float (&d)[32], const uint32_t (&a)[4], uint64_t db, int acc) {
  asm volatile("{\n.reg .pred p;\nsetp.ne.b32 p, %37, 0;\n"
               "wgmma.mma_async.sync.aligned.m64n64k16.f32.bf16.bf16 " REGS32 ", {%32,%33,%34,%35}, %36, p, 1, 1, 1;\n}\n"
               : ACC8(d, 0), ACC8(d, 8), ACC8(d, 16), ACC8(d, 24)
               : "r"(a[0]), "r"(a[1]), "r"(a[2]), "r"(a[3]), "l"(db), "r"(acc));
}
template <uint32_t OFF, uint32_t HI>
__device__ __forceinline__ void wgmma_ss64(float (&d)[32], uint32_t da_lo, uint64_t db) {
  asm volatile("{\n.reg .b32 lo;\n.reg .b64 da;\nadd.u32 lo, %32, %34;\nmov.b64 da, {lo, %35};\n"
               "wgmma.mma_async.sync.aligned.m64n64k16.f32.bf16.bf16 " REGS32 ", da, %33, 1, 1, 1, 0, 1;\n}\n"
               : ACC8(d, 0), ACC8(d, 8), ACC8(d, 16), ACC8(d, 24)
               : "r"(da_lo), "l"(db), "n"(OFF), "n"(HI));
}
__device__ __forceinline__ void wgmma_rs24(float (&d)[12], const uint32_t (&a)[4], uint64_t db, int acc) {
  asm volatile("{\n.reg .pred p;\nsetp.ne.b32 p, %17, 0;\n"
               "wgmma.mma_async.sync.aligned.m64n24k16.f32.bf16.bf16 {%0,%1,%2,%3,%4,%5,%6,%7,%8,%9,%10,%11}, {%12,%13,%14,%15}, %16, p, 1, 1, 1;\n}\n"
               : ACC8(d, 0), "+f"(d[8]), "+f"(d[9]), "+f"(d[10]), "+f"(d[11])
               : "r"(a[0]), "r"(a[1]), "r"(a[2]), "r"(a[3]), "l"(db), "r"(acc));
}
__device__ __forceinline__ void wgmma_ss40tt(float (&d)[20], uint64_t da, uint64_t db, int acc) {
  asm volatile("{\n.reg .pred p;\nsetp.ne.b32 p, %22, 0;\n"
               "wgmma.mma_async.sync.aligned.m64n40k16.f32.bf16.bf16 {%0,%1,%2,%3,%4,%5,%6,%7,%8,%9,%10,%11,%12,%13,%14,%15,%16,%17,%18,%19}, %20, %21, p, 1, 1, 1, 1;\n}\n"
               : ACC8(d, 0), ACC8(d, 8), "+f"(d[16]), "+f"(d[17]), "+f"(d[18]), "+f"(d[19])
               : "l"(da), "l"(db), "r"(acc));
}
template <uint32_t OFF, uint32_t HI, int ACCUM>
__device__ __forceinline__ void wgmma_ss16(float (&d)[8], uint32_t da_lo, uint64_t db) {
  asm volatile("{\n.reg .b32 lo;\n.reg .b64 da;\n.reg .pred p;\nsetp.ne.b32 p, %12, 0;\nadd.u32 lo, %8, %10;\nmov.b64 da, {lo, %11};\n"
               "wgmma.mma_async.sync.aligned.m64n16k16.f32.bf16.bf16 {%0,%1,%2,%3,%4,%5,%6,%7}, da, %9, p, 1, 1, 0, 1;\n}\n"
               : ACC8(d, 0)
               : "r"(da_lo), "l"(db), "n"(OFF), "n"(HI), "n"(ACCUM));
}
template <int N> __device__ __forceinline__ void pin(float (&d)[N]) {
#pragma unroll
  for (int i = 0; i < N; i++) asm volatile("" : "+f"(d[i])::"memory");
}

__device__ __forceinline__ void pin8(float (&d)[32], const int o) { asm volatile("" : ACC8(d, o)::"memory"); }

template <int I> struct IC { static constexpr int value = I; };
template <int I, int N, class F> __device__ __forceinline__ void static_for(F f) {
  if constexpr (I < N) { f(IC<I>()); static_for<I + 1, N>(f); }
}

struct Params {
  const __nv_bfloat16* x;
  const __nv_bfloat16* wqkv;
  const __nv_bfloat16* wo;
  const __nv_bfloat16* w1;
  const __nv_bfloat16* w3;
  const __nv_bfloat16* w2;
  __nv_bfloat16* out;
};

__global__ void __launch_bounds__(NTHREADS, 1)
fused_block_kernel(const __grid_constant__ CUtensorMap m_qkv, const __grid_constant__ CUtensorMap m_w1,
                   const __grid_constant__ CUtensorMap m_w3, const __grid_constant__ CUtensorMap m_w2,
                   const __grid_constant__ CUtensorMap m_M, const __grid_constant__ CUtensorMap m_x,
                   const __grid_constant__ CUtensorMap m_l, const Params p) {
  extern __shared__ __align__(1024) uint8_t smem_raw[];
  constexpr uint32_t sb = 1024;
  if ((uint32_t)__cvta_generic_to_shared(smem_raw) != sb) __trap();
  const int tid = threadIdx.x, warp = __shfl_sync(0xffffffffu, tid >> 5, 0), lane = tid & 31;
  const int r = blockIdx.x >> 3, j = blockIdx.x & 7;

  GT(0); TSC(0);
  if (tid < 144) {
    if (warp > 0) {
      const uint32_t t0 = clock();
      while ((uint32_t)clock() - t0 < (uint32_t)warp * XPD) {}
    }
    asm volatile("prefetch.global.L2 [%0];\n" ::"l"(p.x + (size_t)(blockIdx.x * 16 + (tid & 15)) * D_ + (tid >> 4) * 64));
  }
  const int cmain = 72 * j + 8 * (j & 1);
  if (__builtin_expect(warp >= 8, 1)) {
    asm volatile("setmaxnreg.dec.sync.aligned.u32 24;\n");
    if (__builtin_expect(warp == 8, 1)) {
      if (elect_one()) {
#pragma unroll
        for (int b = 0; b < 9; b++) mbar_init(sb + B_X + 8 * b, 1);
        asm volatile("fence.mbarrier_init.release.cluster;\n" ::: "memory");
        mbar_expect(sb + B_X, 16384);
        tma2d(sb + HB, &m_x, 0, 128 * r, sb + B_X);
      }
      __syncwarp();
      asm volatile("bar.arrive 0, 384;\n" ::: "memory");
      TS(2, 20);
      if (elect_one()) {
#pragma unroll
        for (int b = 1; b < 9; b++) {
          mbar_expect(sb + B_X + 8 * b, 16384);
          tma2d(sb + HB + b * 16384, &m_x, 64 * b, 128 * r, sb + B_X + 8 * b);
        }
      }
      __syncwarp();
      TS(2, 21);
      asm volatile("bar.sync 4, 64;\n" ::: "memory");
      if (elect_one()) {
#pragma unroll
        for (int s = 0; s < 6; s++) {
          if (s == WDELAY) mbar_wait(sb + B_X + 8 * XWAIT, 0);
          mbar_expect(sb + B_FULL + 8 * s, SLOT);
          tma2d(sb + s * SLOT, &m_qkv, D_ + cmain, 96 * s, sb + B_FULL + 8 * s);
        }
        const CUtensorMap* mpf = (r & 1) ? &m_w3 : &m_w1;
        if (r < 6) tma2d_prefetch(&m_qkv, 2 * D_ + cmain, 96 * r);
        if (r < 12) { tma2d_prefetch(mpf, 576 * j, 96 * (r >> 1)); tma2d_prefetch(mpf, 576 * j + 32, 96 * (r >> 1)); }
#pragma unroll
        for (int s = 0; s < 6; s++) {
          mbar_wait(sb + B_EMPTY + 8 * s, 0);
          mbar_expect(sb + B_FULL + 8 * s, SLOT);
          tma2d(sb + s * SLOT, &m_qkv, 2 * D_ + cmain, 96 * s, sb + B_FULL + 8 * s);
        }
#pragma unroll 1
        for (int n = 0; n < 18; n++) {
          const int col = 576 * j + 32 * n;
          if (n < 16) { if (r < 12) tma2d_prefetch(mpf, col + 64, 96 * (r >> 1)); }
          else if (r < 6) {
            if (n == 16) tma2d_prefetch(&m_qkv, cmain, 96 * r);
            else tma2d_prefetch(&m_w2, 512, 576 * j + 96 * r);
          }
#pragma unroll
          for (int s = 0; s < 6; s++) {
            mbar_wait(sb + B_EMPTY + 8 * s, (n & 1) ^ 1);
            mbar_expect(sb + B_FULL + 8 * s, SLOT);
            tma2d(sb + s * SLOT, &m_w1, col, 96 * s, sb + B_FULL + 8 * s);
            tma2d(sb + s * SLOT + SLOT / 2, &m_w3, col, 96 * s, sb + B_FULL + 8 * s);
          }
        }
        if (r < 6) tma2d_prefetch(&m_w2, 64 * ((j + 1) & 7), 576 * j + 96 * r);
#pragma unroll
        for (int s = 0; s < 6; s++) {
          mbar_wait(sb + B_EMPTY + 8 * s, 1);
          mbar_expect(sb + B_FULL + 8 * s, SLOT);
          tma2d(sb + s * SLOT, &m_qkv, cmain, 96 * s, sb + B_FULL + 8 * s);
        }
#pragma unroll 1
        for (int n = 0; n < 9; n++) {
          const int col = n == 0 ? 512 : 64 * ((j + n) & 7);
          if (n < 7 && r < 6) tma2d_prefetch(&m_w2, 64 * ((j + n + 2) & 7), 576 * j + 96 * r);
#pragma unroll
          for (int s = 0; s < 6; s++) {
            mbar_wait(sb + B_EMPTY + 8 * s, n & 1);
            mbar_expect(sb + B_FULL + 8 * s, SLOT);
            tma2d(sb + s * SLOT, &m_w2, col, 576 * j + 96 * s, sb + B_FULL + 8 * s);
          }
          if (n == 0) {
            mbar_wait(sb + B_HFREE, 0);
            mbar_wait(sb + B_MRDY, 0);
            asm volatile("fence.proxy.async;\n" ::: "memory");
          }
          mbar_wait(sb + B_EMPTY + 48, (n & 1) ^ 1);
          mbar_expect(sb + B_FULL + 48, 80 * 128);
          tma2d(sb + WO_SLOT, &m_M, col, 80 * j, sb + B_FULL + 48);
          if (n == 4) {
            mbar_expect(sb + B_X, 16384);
            tma2d(sb + XT, &m_x, 64 * j, 128 * r, sb + B_X);
          }
        }
      }
    } else {
      const int ht = tid - 288;
      if (warp == 9) {
        if (elect_one()) {
          asm volatile("prefetch.tensormap [%0];\n" ::"l"(&m_qkv) : "memory");
#pragma unroll
          for (int i = 9; i < 29; i++) mbar_init(sb + BARS + 8 * i, i < 16 ? 1 : i < 26 ? 8 : i == 26 ? 4 : 96);
          asm volatile("fence.mbarrier_init.release.cluster;\n" ::: "memory");
        }
        __syncwarp();
        asm volatile("bar.arrive 4, 64;\n" ::: "memory");
      }
      asm volatile("bar.sync 0, 384;\n" ::: "memory");
      const uint32_t ep = g_epoch[blockIdx.x] + 1;
      mbar_wait(sb + B_X + 8 * 8, 0);
      if (ht < 90) {
        const int e = ht / 18, c = ht - e * 18;
        const __nv_bfloat16* w = p.wo + (size_t)(72 * j + 18 * (r >> 2) + e) * D_ + 144 * (r & 3) + c * 8;
#pragma unroll
        for (int i = 0; i < 4; i++)
          if (i < 3 || ht < 54) cp_async16(sb + WOB + ht * 16 + i * 90 * 16, w + i * 5 * D_);
      }
      const int cl = 72 * j + ((j & 1) ? 0 : 64);
      const __nv_bfloat16* wl = p.wqkv + (size_t)ht * (3 * D_) + cl;
      mbar_wait(sb + B_XDONE, 0);
      if (LTMA > 0 && warp == 11 && elect_one()) {
        asm volatile("mbarrier.expect_tx.shared::cta.b64 [%0], %1;\n" ::"r"(sb + B_LFULL), "r"(LTMA * 9216) : "memory");
#pragma unroll
        for (int m = 0; m < 3; m++)
#pragma unroll
          for (int g = 3 - LTMA; g < 3; g++) tma2d(sb + L24_T + g * 9216 + m * 3072, &m_l, cl + (g == 2 ? 0 : (g + 1) * D_), 192 * m, sb + B_LFULL);
      }
#pragma unroll
      for (int g = 0; g < 3 - LTMA; g++)
#pragma unroll
        for (int m = 0; m < 6; m++) cp_async16(sb + L24_T + g * 9216 + m * 96 * 16 + ht * 16, wl + (size_t)m * 96 * 3 * D_ + (g == 2 ? 0 : (g + 1) * D_));
      if (ht < 64) {
#pragma unroll
        for (int i = 0; i < 4; i++) sts128(sb + V_T - 2048 + (i >> 1) * 20480 + (i & 1) * 1024 + ht * 16, 0x3F803F80u, 0x3F803F80u, 0x3F803F80u, 0x3F803F80u);
      }
      asm volatile("cp.async.wait_all;\n" ::: "memory");
      fence_async_smem();
      mbar_arrive(sb + B_LFULL);
      if (warp == 9) TS(3, 1);

      if (ht == 0) {
        mbar_wait(sb + B_KVD, 0);
        red_rel(&g_cnt1[j * 32]);
        wait_ge(&g_cnt1[j * 32], 16 * ep);
      }
      bar_sync(3, 96);
      if (warp == 9) TS(3, 4);
#pragma unroll 1
      for (int i = ht; i < 171; i += 96) {
        const int dp = i / 19, el = i - dp * 19, hd = r >> 2, w = hd >> 1;
        const int d = 18 * hd + 2 * dp - 32 * w;
        const int m = el == 18 ? 56 * w : 18 * hd + el + 8 - 24 * w;
        const float2* src = reinterpret_cast<const float2*>(g_kvp + j * 16 * 1280 + ((w * 4 + (m >> 4)) * 5 + (d >> 3)) * 32 + (m & 7) * 4 + ((d & 7) >> 1)) + ((m >> 3) & 1);
        float s0 = 0.f, s1 = 0.f;
#pragma unroll 1
        for (int r4 = 0; r4 < 4; r4++) {
          const float2 v0 = __ldcg(src), v1 = __ldcg(src + 2560), v2 = __ldcg(src + 2 * 2560), v3 = __ldcg(src + 3 * 2560);
          s0 += (v0.x + v1.x) + (v2.x + v3.x);
          s1 += (v0.y + v1.y) + (v2.y + v3.y);
          src += 4 * 2560;
        }
        sts64(sb + KVS + dp * 160 + el * 8, __float_as_uint(s0), __float_as_uint(s1));
        if ((r & 3) == 0 && el == 18) *reinterpret_cast<float2*>(g_z + j * 72 + hd * 18 + dp * 2) = make_float2(s0, s1);
      }
      bar_sync(3, 96);
      if (warp == 9) TS(3, 5);
#pragma unroll 1
      for (int t = ht; t < 648; t += 96) {
        const int dp = t / 72, cp = t - dp * 72;
        float c0 = 0.f, c1 = 0.f, c2 = 0.f, c3 = 0.f;
        const uint32_t ka = sb + KVS + dp * 160, wa = sb + WOB + cp * 4;
#pragma unroll
        for (int e2 = 0; e2 < 9; e2++) {
          uint32_t a0, a1, a2, a3;
          lds128(a0, a1, a2, a3, ka + e2 * 16);
          const uint32_t w0 = lds32(wa + e2 * 576), w1 = lds32(wa + e2 * 576 + 288);
          c0 = fmaf(__uint_as_float(a0), blo(w0), c0); c1 = fmaf(__uint_as_float(a0), bhi(w0), c1);
          c2 = fmaf(__uint_as_float(a1), blo(w0), c2); c3 = fmaf(__uint_as_float(a1), bhi(w0), c3);
          c0 = fmaf(__uint_as_float(a2), blo(w1), c0); c1 = fmaf(__uint_as_float(a2), bhi(w1), c1);
          c2 = fmaf(__uint_as_float(a3), blo(w1), c2); c3 = fmaf(__uint_as_float(a3), bhi(w1), c3);
        }
        const int d = 18 * (r >> 2) + 2 * dp;
        uint32_t* dst = reinterpret_cast<uint32_t*>(g_M) + (80 * j + ((j & 1) ? (d < 8 ? d + 64 : d - 8) : d)) * 288 + 72 * (r & 3) + cp;
        dst[0] = pack2(c0, c1);
        dst[288] = pack2(c2, c3);
      }
      asm volatile("fence.proxy.async;\n" ::: "memory");
      bar_sync(3, 96);
      if (warp == 9) TS(3, 6);
      if (ht == 0) { red_rel(&g_cnt2[j * 32]); wait_ge(&g_cnt2[j * 32], 16 * ep); }
      bar_sync(3, 96);
      if (ht < 80) {
        const int d = (j & 1) ? (ht < 64 ? ht + 8 : ht - 64) : ht;
        uint32_t zb = 0;
        if (ht < 72) zb = pack2(__ldcg(g_z + j * 72 + d), 0.f);
        const int hd = d / 18;
        const uint32_t w = (hd & 1) ? zb << 16 : zb;
        const uint32_t w0 = hd < 2 ? w : 0u, w1 = hd < 2 ? 0u : w;
        sts128(sb + ZM + ht * 16, w0, w0, w0, w0);
        sts128(sb + ZM + 1280 + ht * 16, w1, w1, w1, w1);
      }
      const uint32_t tag = (ep & 1) << 16;
      if (ht == 95) { sts32(sb + TAGW, tag); g_epoch[blockIdx.x] = ep; }
      fence_async_smem();
      mbar_arrive(sb + B_MRDY);
      if (warp == 9) TS(3, 7);
      if (warp < 11) {
        mbar_wait(sb + B_FULL + 48, 0);
#pragma unroll 1
        for (int i = warp - 9; i < 4; i += 2) {
          const uint4* src = g_part + (size_t)((r * 9 + 8) * 8) * 1024 + j * 128 + i * 32 + lane;
          const int off = ((r * 128 + j * 16 + (lane >> 2)) * D_ + 512 + 16 * i + 2 * (lane & 3)) >> 1;
          float s0, s1, s2, s3, s4, s5, s6, s7;
          {
            const uint32_t* xp = reinterpret_cast<const uint32_t*>(p.x) + off;
            const uint32_t x0 = __ldg(xp), x1 = __ldg(xp + 4 * D_), x2 = __ldg(xp + 4), x3 = __ldg(xp + 4 * D_ + 4);
            s0 = blo(x0); s1 = bhi(x0); s2 = blo(x1); s3 = bhi(x1); s4 = blo(x2); s5 = bhi(x2); s6 = blo(x3); s7 = bhi(x3);
          }
          uint32_t n = 0;
#pragma unroll 1
          for (int jj = 0; jj < 8;) {
            uint32_t v0, v1, v2, v3;
            ld_b128(v0, v1, v2, v3, src);
            if (__all_sync(0xffffffffu, ((v0 ^ tag) & 0x10000u) == 0)) {
              s0 += blo(v0); s1 += __uint_as_float(v0 & 0xfffe0000u); s2 += blo(v1); s3 += bhi(v1);
              s4 += blo(v2); s5 += bhi(v2); s6 += blo(v3); s7 += bhi(v3);
              jj++;
              src += 1024;
            } else {
              __nanosleep(200);
              if (++n > SPIN_LIMIT) __trap();
            }
          }
          uint32_t* op = reinterpret_cast<uint32_t*>(p.out) + off;
          op[0] = pack2(s0, s1); op[4 * D_] = pack2(s2, s3); op[4] = pack2(s4, s5); op[4 * D_ + 4] = pack2(s6, s7);
        }
        if (warp == 9) TS(3, 10);
      }
    }
  } else {
    asm volatile("setmaxnreg.inc.sync.aligned.u32 240;\n");
    asm volatile("bar.sync 0, 384;\n" ::: "memory");
    const int wg = warp >> 2;
    uint32_t a[36][4];
    float dA[32], dB[32];
    const bool l0 = lane == 0;
    constexpr uint64_t dsw128 = mkdesc(sb, 16, 1024, 1);
    constexpr uint64_t dsw64 = mkdesc(sb, SLOT / 2, 512, 2);

    auto issue = [&](float (&d)[32], const uint64_t dbase, const int kstride, const int s, const uint32_t ph, const int init = 0) {
      mbar_wait(sb + B_FULL + 8 * s, ph);
      wg_fence();
#pragma unroll
      for (int ks = 0; ks < 6; ks++) wgmma_rs64(d, a[s * 6 + ks], dbase + ((s * SLOT + ks * kstride) >> 4), (s | ks | init) != 0);
    };
    auto finish = [&](const int rel) {
      wg_commit();
      wg_wait<1>();
      if (rel >= 0 && l0) mbar_arrive(sb + B_EMPTY + 8 * rel);
    };
    auto stW = [&](float (&d)[32], const int s, const uint32_t ph, const int rel) { issue(d, dsw128, 2048, s, ph); finish(rel); };
    auto stF = [&](float (&d)[32], const int s, const uint32_t ph, const int rel) { issue(d, dsw64, 1024, s, ph); finish(rel); };

    TSC(1);
    uint32_t mb0, mb1;
    float r0, r1;
    auto center = [&](const int g) {
#pragma unroll
      for (int ks = 6 * g; ks < 6 * g + 6; ks++) {
        a[ks][0] = bsub2(a[ks][0], mb0); a[ks][1] = bsub2(a[ks][1], mb1);
        a[ks][2] = bsub2(a[ks][2], mb0); a[ks][3] = bsub2(a[ks][3], mb1);
        asm volatile("" : "+r"(a[ks][0]), "+r"(a[ks][1]), "+r"(a[ks][2]), "+r"(a[ks][3])::"memory");
      }
    };
    {
      const uint32_t xa = sb + HB + (warp * 16 + (lane & 15)) * 128;
      const uint32_t sw = lane & 7, hi = lane >> 4;
      constexpr uint32_t ONES = 0x3F803F80u;
      float cs[2][4], cq[2][4];
#pragma unroll
      for (int i = 0; i < 4; i++) { cs[0][i] = cs[1][i] = cq[0][i] = cq[1][i] = 0.f; }
      auto rsum = [&](const int ks) { mma16816(cs[ks & 1], a[ks][0], a[ks][1], a[ks][2], a[ks][3], ONES, ONES); };
      auto rsq = [&](const int ks) {
        mma16816(cq[ks & 1], bmul2(a[ks][0], a[ks][0]), bmul2(a[ks][1], a[ks][1]), bmul2(a[ks][2], a[ks][2]), bmul2(a[ks][3], a[ks][3]), ONES, ONES);
      };
#pragma unroll
      for (int b = 0; b < 9; b++) {
        mbar_wait(sb + B_X + 8 * b, 0);
        if (b == 0 || b == 8) TSC(32 + b);
#pragma unroll
        for (int kk = 0; kk < 4; kk++) ldsm4(a[4 * b + kk][0], a[4 * b + kk][1], a[4 * b + kk][2], a[4 * b + kk][3], xa + b * 16384 + (((2 * kk + hi) ^ sw) << 4));
        if (b > 0) {
#pragma unroll
          for (int ks = 4 * b - 4; ks < 4 * b; ks++) { rsum(ks); rsq(ks); }
        }
      }
      __syncwarp();
      if (l0) mbar_arrive(sb + B_XDONE);
#pragma unroll
      for (int ks = 32; ks < 36; ks++) rsum(ks);
#pragma unroll
      for (int ks = 32; ks < 36; ks++) rsq(ks);
      TSC(2);
      const float m0 = (cs[0][0] + cs[1][0]) * (1.f / 576.f), m1 = (cs[0][2] + cs[1][2]) * (1.f / 576.f);
      mb0 = pack2(m0, m0);
      mb1 = pack2(m1, m1);
      center(0);
      TSC(3);
      stW(dA, 0, 0, -1);
      center(1);
      stW(dA, 1, 0, 0);
      const float q0 = (cq[0][0] + cq[1][0]) * (1.f / 576.f), q1 = (cq[0][2] + cq[1][2]) * (1.f / 576.f);
      float v0 = q0 - m0 * m0, v1 = q1 - m1 * m1;
      if (__any_sync(0xffffffffu, v0 < q0 * 0.5f || v1 < q1 * 0.5f)) {
        float s0 = 0.f, s1 = 0.f;
        const uint32_t* xr = reinterpret_cast<const uint32_t*>(p.x + (size_t)(r * 128 + warp * 16 + (lane >> 2)) * D_) + (lane & 3);
#pragma unroll 4
        for (int i = 0; i < 72; i++) {
          const uint32_t e0 = __ldg(xr + 4 * i), e1 = __ldg(xr + 4 * D_ + 4 * i);
          float t;
          t = blo(e0) - m0; s0 = fmaf(t, t, s0); t = bhi(e0) - m0; s0 = fmaf(t, t, s0);
          t = blo(e1) - m1; s1 = fmaf(t, t, s1); t = bhi(e1) - m1; s1 = fmaf(t, t, s1);
        }
        s0 += __shfl_xor_sync(0xffffffffu, s0, 1); s1 += __shfl_xor_sync(0xffffffffu, s1, 1);
        s0 += __shfl_xor_sync(0xffffffffu, s0, 2); s1 += __shfl_xor_sync(0xffffffffu, s1, 2);
        v0 = s0 * (1.f / 576.f); v1 = s1 * (1.f / 576.f);
      }
      r0 = rcp(rbf(sqrta(rbf(rbf(fmaxf(v0, 0.f)) + 1e-5f))));
      r1 = rcp(rbf(sqrta(rbf(rbf(fmaxf(v1, 0.f)) + 1e-5f))));
    }
#pragma unroll
    for (int s = 2; s < 6; s++) {
      center(s);
      stW(dA, s, 0, s - 1);
    }
    TSC(4); GT(1);
    constexpr float LOG2E = 1.4426950408889634f;
    float l0e = r0 * LOG2E, l1e = r1 * LOG2E;
    const uint32_t tile_off = ((lane >> 4) + (j & 1)) * 2048 + (warp * 16 + (lane & 15)) * 16;
    mbar_wait(sb + B_XDONE, 0);
#pragma unroll
    for (int s = 0; s < 6; s++) {
      stW(dB, s, 1, (s + 5) % 6);
      TSC(50 + s);
      if (s < 4) {
        const int t = 2 * s;
        pin8(dA, 4 * t);
        stsm4(sb + PK_T + tile_off + t * 2048, pack2(phi(dA[4 * t], r0, l0e), phi(dA[4 * t + 1], r0, l0e)), pack2(phi(dA[4 * t + 2], r1, l1e), phi(dA[4 * t + 3], r1, l1e)),
              pack2(phi(dA[4 * t + 4], r0, l0e), phi(dA[4 * t + 5], r0, l0e)), pack2(phi(dA[4 * t + 6], r1, l1e), phi(dA[4 * t + 7], r1, l1e)));
      }
    }
    TSC(5);
    {
#pragma unroll
      for (int s = 0; s < 2; s++) {
        stF(dA, s, 0, (s + 5) % 6);
#pragma unroll
        for (int t = 4 * s; t < 4 * s + 4; t += 2) {
          pin8(dB, 4 * t);
          stsm4(sb + V_T + tile_off + t * 2048, pack2(dB[4 * t] * r0, dB[4 * t + 1] * r0), pack2(dB[4 * t + 2] * r1, dB[4 * t + 3] * r1),
                pack2(dB[4 * t + 4] * r0, dB[4 * t + 5] * r0), pack2(dB[4 * t + 6] * r1, dB[4 * t + 7] * r1));
        }
      }
      float dL[12];
      constexpr uint64_t dl = mkdesc(sb + L24_T, 128, 576 * 16, 0);
      mbar_wait(sb + B_LFULL, 0);
#pragma unroll
      for (int s = 2; s < 5; s++) {
        mbar_wait(sb + B_FULL + 8 * s, 0);
        wg_fence();
#pragma unroll
        for (int ks = 12 * (s - 2); ks < 12 * (s - 1); ks++) wgmma_rs24(dL, a[ks], dl + ks * 16, ks != 0);
#pragma unroll
        for (int ks = 0; ks < 6; ks++) wgmma_rs64(dA, a[s * 6 + ks], dsw64 + ((s * SLOT + ks * 1024) >> 4), 1);
        finish(s - 1);
      }
      stF(dA, 5, 0, 4);
      pin(dL);
      const uint32_t lo = ((j & 1) ? 0 : 8 * 2048) + warp * 256 + lane * 4;
      sts32(sb + PK_T + lo, pack2(phi(dL[0], r0, l0e), phi(dL[1], r0, l0e)));
      sts32(sb + PK_T + lo + 128, pack2(phi(dL[2], r1, l1e), phi(dL[3], r1, l1e)));
      sts32(sb + V_T + lo, pack2(dL[4] * r0, dL[5] * r0));
      sts32(sb + V_T + lo + 128, pack2(dL[6] * r1, dL[7] * r1));
      sts64(sb + Q8 + tid * 8, pack2(dL[8], dL[9]), pack2(dL[10], dL[11]));
      fence_async_smem();
      __syncwarp();
      if (l0) mbar_arrive(sb + B_KVT);
    }
    TSC(6);
    uint32_t hs = sb + HB + wg * HHALF + (tid & 127) * 16;
    uint32_t hp0, hp1;
    const float iq0 = rcp(r0 * r0), iq1 = rcp(r1 * r1);
    auto epiF = [&](float (&d)[32], const int pc) {
      asm volatile("" : "+f"(d[4 * pc]), "+f"(d[4 * pc + 1]), "+f"(d[4 * pc + 2]), "+f"(d[4 * pc + 3]), "+f"(d[4 * pc + 16]), "+f"(d[4 * pc + 17]),
                   "+f"(d[4 * pc + 18]), "+f"(d[4 * pc + 19])::"memory");
      const float g0 = d[4 * pc], g1 = d[4 * pc + 1], g2 = d[4 * pc + 2], g3 = d[4 * pc + 3];
      const uint32_t h0 = pack2(g0 * d[4 * pc + 16] * rcp(fmaf(ex2(-g0 * l0e), iq0, iq0)), g1 * d[4 * pc + 17] * rcp(fmaf(ex2(-g1 * l0e), iq0, iq0)));
      const uint32_t h1 = pack2(g2 * d[4 * pc + 18] * rcp(fmaf(ex2(-g2 * l1e), iq1, iq1)), g3 * d[4 * pc + 19] * rcp(fmaf(ex2(-g3 * l1e), iq1, iq1)));
      if (pc & 1) {
        sts128(hs, hp0, hp1, h0, h1);
        hs += 2048;
      } else {
        hp0 = h0; hp1 = h1;
        asm volatile("" : "+r"(hp0), "+r"(hp1)::"memory");
      }
    };
    {
      stF(dB, 0, 1, 5);
      epiF(dA, 0); epiF(dA, 1);
      stF(dB, 1, 1, 0);
      epiF(dA, 2); epiF(dA, 3);
      float dK[20];
      const uint64_t ka = mkdesc(sb + V_T - 2048 + wg * 3 * 2048, 128, 2048, 0), kb = mkdesc(sb + PK_T + wg * 4 * 2048, 128, 2048, 0);
      mbar_wait(sb + B_KVT, 0);
      mbar_wait(sb + B_FULL + 8 * 2, 1);
      wg_fence();
#pragma unroll
      for (int ks = 0; ks < 8; ks++) wgmma_ss40tt(dK, ka + ks * 16, kb + ks * 16, ks != 0);
#pragma unroll
      for (int ks = 0; ks < 6; ks++) wgmma_rs64(dB, a[12 + ks], dsw64 + ((2 * SLOT + ks * 1024) >> 4), 1);
      finish(1);
      stF(dB, 3, 1, 2);
      pin(dK);
      float4* dst = g_kvp + (j * 16 + r) * 1280 + warp * 160 + lane;
#pragma unroll
      for (int t = 0; t < 5; t++) __stcg(dst + t * 32, make_float4(dK[4 * t], dK[4 * t + 1], dK[4 * t + 2], dK[4 * t + 3]));
      __syncwarp();
      if (l0) mbar_arrive(sb + B_KVD);
      stF(dB, 4, 1, 3);
    }
#pragma unroll 1
    for (int it = 0; it < 8; it++) {
      stF(dB, 5, 1, 4);
      stF(dA, 0, 0, 5);
#pragma unroll
      for (int s = 1; s < 5; s++) { epiF(dB, s - 1); stF(dA, s, 0, s - 1); }
      stF(dA, 5, 0, 4);
      stF(dB, 0, 1, 5);
#pragma unroll
      for (int s = 1; s < 5; s++) { epiF(dA, s - 1); stF(dB, s, 1, s - 1); }
      TSC(7 + it);
    }
    stF(dB, 5, 1, 4);
    TSC(15);
    const uint32_t hl = sb + HB + wg * HHALF + (tid & 127) * 16;
    auto reload = [&](auto k0, auto k1) {
      static_for<decltype(k0)::value, decltype(k1)::value>([&](auto k) { lds128_inplace<decltype(k)::value * 2048>(a[decltype(k)::value], hl); });
    };
    stW(dA, 0, 0, 5);
    epiF(dB, 0);
    stW(dA, 1, 0, 0);
    reload(IC<0>(), IC<4>());
    epiF(dB, 1);
    stW(dA, 2, 0, 1);
    reload(IC<4>(), IC<8>());
    epiF(dB, 2);
    stW(dA, 3, 0, 2);
    reload(IC<8>(), IC<12>());
    __syncwarp();
    if (l0 && wg == 0) mbar_arrive(sb + B_HFREE);
    epiF(dB, 3);
    stW(dA, 4, 0, 3);
    reload(IC<12>(), IC<17>());
    stW(dA, 5, 0, 4);
    reload(IC<17>(), IC<22>());
    const uint32_t ot = sb + HB + wg * HHALF;
    const uint32_t do_a = (uint32_t)mkdesc(ot, 128, 1280, 0);
    constexpr uint64_t do_b = mkdesc(sb + WO_SLOT, 16, 1024, 1);
    auto stO = [&](float (&d)[32], const uint32_t ph, const int rel) {
      mbar_wait(sb + B_FULL + 48, ph);
      wg_fence();
      wgmma_ss64<0, 80>(d, do_a, do_b);
      wgmma_ss64<16, 80>(d, do_a, do_b + 128);
      wgmma_ss64<32, 80>(d, do_a, do_b + 256);
      wgmma_ss64<48, 80>(d, do_a, do_b + 384);
      wgmma_ss64<64, 80>(d, do_a, do_b + 512);
      finish(rel);
    };
    uint32_t tag;
    auto epiP = [&](float (&d)[32], const int step) {
      pin(d);
      const int c = step == 0 ? 8 : ((j + step) & 7);
      uint4* dst = g_part + (size_t)((r * 9 + c) * 8 + j) * 1024 + warp * 128 + lane;
#pragma unroll
      for (int i = 0; i < 4; i++)
        st_b128(dst + i * 32, (pack2(d[8 * i], d[8 * i + 1]) & 0xfffeffffu) | tag, pack2(d[8 * i + 2], d[8 * i + 3]), pack2(d[8 * i + 4], d[8 * i + 5]), pack2(d[8 * i + 6], d[8 * i + 7]));
    };
    TSC(16);
    {
      stW(dB, 0, 1, 5);
      reload(IC<22>(), IC<26>());
      asm volatile("" : "+f"(l0e), "+f"(l1e));
      r0 = l0e * (1.f / LOG2E); r1 = l1e * (1.f / LOG2E);
      uint32_t pq[18];
      const uint32_t oa = ot + ((warp & 3) * 2 + ((lane >> 3) & 1)) * 1280 + (lane >> 4) * 128 + (lane & 7) * 16;
      auto phiq = [&](const int t0, const int t1) {
#pragma unroll
        for (int t = t0; t < t1; t++) {
          asm volatile("" : "+f"(dA[4 * t]), "+f"(dA[4 * t + 1]), "+f"(dA[4 * t + 2]), "+f"(dA[4 * t + 3])::"memory");
          pq[2 * t] = pack2(phi(dA[4 * t], r0, l0e), phi(dA[4 * t + 1], r0, l0e));
          pq[2 * t + 1] = pack2(phi(dA[4 * t + 2], r1, l1e), phi(dA[4 * t + 3], r1, l1e));
          asm volatile("" : "+r"(pq[2 * t]), "+r"(pq[2 * t + 1])::"memory");
        }
      };
      phiq(0, 3);
      bar_sync(1 + wg, 128);
      stW(dB, 1, 1, 0);
      reload(IC<26>(), IC<30>());
      phiq(3, 6);
      stW(dB, 2, 1, 1);
      phiq(6, 8);
      {
        uint32_t q0, q1;
        lds64(q0, q1, sb + Q8 + tid * 8);
        pq[16] = pack2(phi(blo(q0), r0, l0e), phi(bhi(q0), r0, l0e));
        pq[17] = pack2(phi(blo(q1), r1, l1e), phi(bhi(q1), r1, l1e));
      }
#pragma unroll
      for (int t = 0; t < 8; t += 2) stsm4(oa + t * 128, pq[2 * t], pq[2 * t + 1], pq[2 * t + 2], pq[2 * t + 3]);
      stsm4(oa + 1024, pq[16], pq[17], 0u, 0u);
      fence_async_smem();
      TSC(17);
      mbar_wait(sb + B_MRDY, 0);
      TSC(18);
      tag = lds32(sb + TAGW);
      float den[8];
      constexpr uint64_t dz = mkdesc(sb + ZM, 128, 1280, 0);
      bar_sync(1 + wg, 128);
      issue(dB, dsw128, 2048, 3, 1);
      wgmma_ss16<0, 80, 0>(den, do_a, dz);
      wgmma_ss16<16, 80, 1>(den, do_a, dz + 16);
      wgmma_ss16<32, 80, 1>(den, do_a, dz + 32);
      wgmma_ss16<48, 80, 1>(den, do_a, dz + 48);
      wgmma_ss16<64, 80, 1>(den, do_a, dz + 64);
      finish(2);
      reload(IC<30>(), IC<36>());
      stW(dB, 4, 1, 3);
      pin(den);
      uint32_t iv[8];
#pragma unroll
      for (int i = 0; i < 8; i++) { const float t = rcp(den[i] + 1e-6f); iv[i] = pack2(t, t); }
      const int u = 2 * (lane & 3) + 8 * (j & 1);
#pragma unroll
      for (int t = 0; t < 10; t += 2) {
        uint32_t o[4];
#pragma unroll
        for (int z = 0; z < 2; z++) {
          const int tt = t + z;
          if (tt < 9) {
            const int lo = tt == 0 ? 0 : tt >= 7 ? 3 : (tt - 1) >> 1, hi = tt == 8 ? 0 : (tt == 0 || tt == 7) ? lo : lo + 1;
            const bool up = tt == 8 ? (j & 1) : 8 * tt + u >= 18 * hi;
            const int il = (lo >> 1) * 4 + (lo & 1), ih = (hi >> 1) * 4 + (hi & 1);
            o[2 * z] = bmul2(pq[2 * tt], up ? iv[ih] : iv[il]);
            o[2 * z + 1] = bmul2(pq[2 * tt + 1], up ? iv[ih + 2] : iv[il + 2]);
          } else {
            o[2 * z] = 0; o[2 * z + 1] = 0;
          }
        }
        stsm4(oa + t * 128, o[0], o[1], o[2], o[3]);
      }
      fence_async_smem();
      stW(dB, 5, 1, 4);
      bar_sync(1 + wg, 128);
      stO(dB, 0, 5);
    }
    stW(dA, 0, 0, 6);
    epiP(dB, 0);
    TSC(19);
    auto ldp = [&](uint32_t (&v)[16], const int c, const int dj) {
      const uint4* src = g_part + (size_t)((r * 9 + c) * 8 + ((j + dj) & 7)) * 1024 + warp * 128 + lane;
#pragma unroll
      for (int i = 0; i < 4; i++) ld_b128(v[4 * i], v[4 * i + 1], v[4 * i + 2], v[4 * i + 3], src + i * 32);
    };
    auto chk = [&](uint32_t (&v)[16], const int c, const int dj) {
      uint32_t n = 0;
      while (__any_sync(0xffffffffu, (((v[0] ^ tag) | (v[4] ^ tag) | (v[8] ^ tag) | (v[12] ^ tag)) & 0x10000u) != 0)) {
        ldp(v, c, dj);
        if (++n > SPIN_LIMIT) asm volatile("trap;");
      }
    };
    auto unp = [&](float (&d)[32], uint32_t (&v)[16], const int i) {
      d[8 * i] = blo(v[4 * i]); d[8 * i + 1] = __uint_as_float(v[4 * i] & 0xfffe0000u); d[8 * i + 2] = blo(v[4 * i + 1]); d[8 * i + 3] = bhi(v[4 * i + 1]);
      d[8 * i + 4] = blo(v[4 * i + 2]); d[8 * i + 5] = bhi(v[4 * i + 2]); d[8 * i + 6] = blo(v[4 * i + 3]); d[8 * i + 7] = bhi(v[4 * i + 3]);
      pin8(d, 8 * i);
    };
#pragma unroll
    for (int s = 1; s < 6; s++) stW(dA, s, 0, s - 1);
    stO(dA, 1, 5);
    stW(dB, 0, 1, 6);
    epiP(dA, 1);
    TSC(20);
#pragma unroll 1
    for (int it = 0; it < 3; it++) {
      uint32_t v[16];
      stW(dB, 1, 1, 0);
#pragma unroll
      for (int i = 0; i < 16; i++) v[i] = (i & 3) ? 0u : tag;
      if (it > 0) ldp(v, (j + 3 + 2 * it) & 7, 3);
      stW(dB, 2, 1, 1);
      stW(dB, 3, 1, 2);
      stW(dB, 4, 1, 3);
      chk(v, (j + 3 + 2 * it) & 7, 3);
      unp(dA, v, 0); unp(dA, v, 1);
      stW(dB, 5, 1, 4);
      unp(dA, v, 2); unp(dA, v, 3);
      stO(dB, 0, 5);
      issue(dA, dsw128, 2048, 0, 0, 1); finish(6);
      epiP(dB, 2 + 2 * it);
      stW(dA, 1, 0, 0);
      ldp(v, (j + 4 + 2 * it) & 7, 3);
      stW(dA, 2, 0, 1);
      stW(dA, 3, 0, 2);
      stW(dA, 4, 0, 3);
      chk(v, (j + 4 + 2 * it) & 7, 3);
      unp(dB, v, 0); unp(dB, v, 1);
      stW(dA, 5, 0, 4);
      unp(dB, v, 2); unp(dB, v, 3);
      stO(dA, 1, 5);
      issue(dB, dsw128, 2048, 0, 1, 1); finish(6);
      epiP(dA, 3 + 2 * it);
      TSC(21 + it);
    }
    {
      uint32_t v[16], w[16], xv[16];
      float f[32] = {};
      auto addv = [&](uint32_t (&v)[16], const int i) {
        f[8 * i] += blo(v[4 * i]); f[8 * i + 1] += __uint_as_float(v[4 * i] & 0xfffe0000u); f[8 * i + 2] += blo(v[4 * i + 1]); f[8 * i + 3] += bhi(v[4 * i + 1]);
        f[8 * i + 4] += blo(v[4 * i + 2]); f[8 * i + 5] += bhi(v[4 * i + 2]); f[8 * i + 6] += blo(v[4 * i + 3]); f[8 * i + 7] += bhi(v[4 * i + 3]);
        pin8(f, 8 * i);
      };
      ldp(v, j, 2);
      stW(dB, 1, 1, -1);
      TSC(44);
      mbar_wait(sb + B_X, 1);
#pragma unroll
      for (int i = 0; i < 4; i++)
        ldsm4(xv[4 * i], xv[4 * i + 1], xv[4 * i + 2], xv[4 * i + 3], sb + XT + (warp * 16 + (lane & 15)) * 128 + (((2 * i + (lane >> 4)) ^ (lane & 7)) << 4));
      stW(dB, 2, 1, -1);
      TSC(45);
#pragma unroll
      for (int i = 0; i < 16; i++) { f[2 * i] = blo(xv[i]); f[2 * i + 1] = bhi(xv[i]); }
      pin(f);
      stW(dB, 3, 1, -1);
      TSC(46);
      chk(v, j, 2);
      ldp(w, j, 1);
      addv(v, 0); addv(v, 1);
      stW(dB, 4, 1, -1);
      TSC(47);
      addv(v, 2); addv(v, 3);
      stW(dB, 5, 1, -1);
      TSC(48);
      chk(w, j, 1);
      TSC(49);
      addv(w, 0); addv(w, 1);
      stO(dB, 0, -1);
      TSC(24);
      addv(w, 2); addv(w, 3);
      TSC(25);
      wg_wait<0>();
      TSC(26); GT(2);
      pin(dB);
      const uint32_t ps = sb + HB + wg * HHALF + STG + (warp & 3) * 2048;
      const int row = lane & 15;
#pragma unroll
      for (int t = 0; t < 8; t += 2)
        stsm4(ps + row * 128 + (((t + (lane >> 4)) ^ (row & 7)) << 4),
              pack2(f[4 * t] + dB[4 * t], f[4 * t + 1] + dB[4 * t + 1]), pack2(f[4 * t + 2] + dB[4 * t + 2], f[4 * t + 3] + dB[4 * t + 3]),
              pack2(f[4 * t + 4] + dB[4 * t + 4], f[4 * t + 5] + dB[4 * t + 5]), pack2(f[4 * t + 6] + dB[4 * t + 6], f[4 * t + 7] + dB[4 * t + 7]));
      __syncwarp();
#pragma unroll
      for (int i = 0; i < 4; i++) {
        const int rr = i * 4 + (lane >> 3), ch = lane & 7;
        uint4 o;
        lds128(o.x, o.y, o.z, o.w, ps + rr * 128 + ((ch ^ (rr & 7)) << 4));
        *reinterpret_cast<uint4*>(p.out + (size_t)(r * 128 + warp * 16 + rr) * D_ + 64 * j + ch * 8) = o;
      }
    }
    TSC(27); GT(3);
  }
}

typedef CUresult (*EncodeFn)(CUtensorMap*, CUtensorMapDataType, cuuint32_t, void*, const cuuint64_t*, const cuuint64_t*, const cuuint32_t*,
                             const cuuint32_t*, CUtensorMapInterleave, CUtensorMapSwizzle, CUtensorMapL2promotion, CUtensorMapFloatOOBfill);

CUtensorMap make_map(EncodeFn enc, const void* ptr, int rows, int cols, int brow, int bcol, CUtensorMapSwizzle sw) {
  CUtensorMap m;
  cuuint64_t gd[2] = {(cuuint64_t)cols, (cuuint64_t)rows};
  cuuint64_t gs[1] = {(cuuint64_t)cols * 2};
  cuuint32_t bd[2] = {(cuuint32_t)bcol, (cuuint32_t)brow};
  cuuint32_t es[2] = {1, 1};
  enc(&m, CU_TENSOR_MAP_DATA_TYPE_BFLOAT16, 2, const_cast<void*>(ptr), gd, gs, bd, es, CU_TENSOR_MAP_INTERLEAVE_NONE, sw,
      CU_TENSOR_MAP_L2_PROMOTION_L2_128B, CU_TENSOR_MAP_FLOAT_OOB_FILL_NONE);
  return m;
}

}

extern "C" void kernel_launch(void* const* d_in, const int* in_sizes, int n_in, void* d_out, int out_size) {
  (void)in_sizes; (void)n_in; (void)out_size;
  static EncodeFn enc = nullptr;
  static void* m_ptr = nullptr;
  if (!enc) {
    cudaGetSymbolAddress(&m_ptr, g_M);
    cudaDriverEntryPointQueryResult qr;
    cudaGetDriverEntryPoint("cuTensorMapEncodeTiled", (void**)&enc, cudaEnableDefault, &qr);
    cudaFuncSetAttribute(fused_block_kernel, cudaFuncAttributeMaxDynamicSharedMemorySize, SMEM_BYTES);
  }
  Params p;
  p.x = (const __nv_bfloat16*)d_in[0];
  p.wqkv = (const __nv_bfloat16*)d_in[1];
  p.wo = (const __nv_bfloat16*)d_in[2];
  p.w1 = (const __nv_bfloat16*)d_in[4];
  p.w3 = (const __nv_bfloat16*)d_in[5];
  p.w2 = (const __nv_bfloat16*)d_in[6];
  p.out = (__nv_bfloat16*)d_out;
  const CUtensorMap m_qkv = make_map(enc, p.wqkv, D_, 3 * D_, 96, 64, CU_TENSOR_MAP_SWIZZLE_128B);
  const CUtensorMap m_w1 = make_map(enc, p.w1, D_, F_, 96, 32, CU_TENSOR_MAP_SWIZZLE_64B);
  const CUtensorMap m_w3 = make_map(enc, p.w3, D_, F_, 96, 32, CU_TENSOR_MAP_SWIZZLE_64B);
  const CUtensorMap m_w2 = make_map(enc, p.w2, F_, D_, 96, 64, CU_TENSOR_MAP_SWIZZLE_128B);
  const CUtensorMap m_M = make_map(enc, m_ptr, 8 * 80, D_, 80, 64, CU_TENSOR_MAP_SWIZZLE_128B);
  const CUtensorMap m_x = make_map(enc, p.x, 2048, D_, 128, 64, CU_TENSOR_MAP_SWIZZLE_128B);
  const CUtensorMap m_l = make_map(enc, p.wqkv, D_, 3 * D_, 192, 8, CU_TENSOR_MAP_SWIZZLE_NONE);
  fused_block_kernel<<<128, NTHREADS, SMEM_BYTES>>>(m_qkv, m_w1, m_w3, m_w2, m_M, m_x, m_l, p);
}
```

```cpp
#include <cuda_runtime.h>
#include <cuda.h>
#include <cuda_bf16.h>
#include <stdint.h>

namespace {

constexpr int D_ = 576, F_ = 4608;
constexpr int NTHREADS = 384;

constexpr uint32_t SLOT = 12288;
constexpr uint32_t HB = 6 * SLOT;
constexpr uint32_t HHALF = 73728;
constexpr uint32_t PK_T = HB + 45056;
constexpr uint32_t V_T = HB + HHALF + 18432;
constexpr uint32_t L24_T = HB + 16384;
constexpr uint32_t WO_SLOT = HB + 12288;
constexpr uint32_t XT = HB + 24576;
constexpr uint32_t STG = 49152;
constexpr uint32_t Q8 = HB + 2 * HHALF;
constexpr uint32_t WOB = Q8 + 2048;
constexpr uint32_t KVS = WOB + 5184;
constexpr uint32_t ZM = WOB;
constexpr uint32_t TAGW = KVS + 1440;
constexpr uint32_t BARS = TAGW + 32;
constexpr uint32_t SMEM_BYTES = BARS + 512;

constexpr uint32_t B_X = BARS;
constexpr uint32_t B_FULL = BARS + 8 * 9;
constexpr uint32_t B_EMPTY = BARS + 8 * 16;
constexpr uint32_t B_XDONE = BARS + 8 * 23;
constexpr uint32_t B_KVT = BARS + 8 * 24;
constexpr uint32_t B_KVD = BARS + 8 * 25;
constexpr uint32_t B_HFREE = BARS + 8 * 26;
constexpr uint32_t B_LFULL = BARS + 8 * 27;
constexpr uint32_t B_MRDY = BARS + 8 * 28;

#define XPF 2
#define LTMA 0
#define WDELAY 2
#define XWAIT 4
constexpr uint32_t SPIN_LIMIT = 1u << 22;

__device__ uint4 g_part[16 * 9 * 8 * 1024];
__device__ float4 g_kvp[8 * 16 * 1280];
__device__ __align__(128) __nv_bfloat16 g_M[8 * 80 * 576];
__device__ __align__(16) float g_z[8 * 72];
__device__ uint32_t g_cnt1[8 * 32], g_cnt2[8 * 32];
__device__ uint32_t g_epoch[128];

#define TS(slot, i)
#define TSC(i)
#define TS1(slot, i)
#define GT(i)

__device__ __forceinline__ void wg_fence() { asm volatile("wgmma.fence.sync.aligned;\n" ::: "memory"); }
__device__ __forceinline__ void wg_commit() { asm volatile("wgmma.commit_group.sync.aligned;\n" ::: "memory"); }
template <int N> __device__ __forceinline__ void wg_wait() { asm volatile("wgmma.wait_group.sync.aligned %0;\n" ::"n"(N) : "memory"); }
__host__ __device__ constexpr uint64_t mkdesc(uint32_t addr, uint32_t lbo, uint32_t sbo, uint32_t sw) {
  return (uint64_t)((addr & 0x3FFFF) >> 4) | ((uint64_t)(lbo >> 4) << 16) | ((uint64_t)(sbo >> 4) << 32) | ((uint64_t)sw << 62);
}
__device__ __forceinline__ void mbar_init(uint32_t a, uint32_t c) { asm volatile("mbarrier.init.shared::cta.b64 [%0], %1;\n" ::"r"(a), "r"(c) : "memory"); }
__device__ __forceinline__ void mbar_expect(uint32_t a, uint32_t b) { asm volatile("mbarrier.arrive.expect_tx.shared::cta.b64 _, [%0], %1;\n" ::"r"(a), "r"(b) : "memory"); }
__device__ __forceinline__ void mbar_arrive(uint32_t a) { asm volatile("mbarrier.arrive.shared::cta.b64 _, [%0];\n" ::"r"(a) : "memory"); }
__device__ __forceinline__ void mbar_wait(uint32_t a, uint32_t ph) {
  asm volatile(
      "{\n.reg .pred p;\n.reg .u32 n;\n"
      "mov.u32 n, 0;\n"
      "LOOP:\n"
      "mbarrier.try_wait.parity.shared::cta.b64 p, [%0], %1;\n"
      "@p bra DONE;\n"
      "add.u32 n, n, 1;\n"
      "setp.gt.u32 p, n, %2;\n"
      "@p trap;\n"
      "bra LOOP;\n"
      "DONE:\n}\n" ::"r"(a), "r"(ph), "n"(SPIN_LIMIT) : "memory");
}
__device__ __forceinline__ void cp_async16(uint32_t dst, const void* src) {
  asm volatile("cp.async.cg.shared.global [%0], [%1], 16;\n" ::"r"(dst), "l"(src) : "memory");
}
__device__ __forceinline__ void tma2d(uint32_t dst, const CUtensorMap* m, int c0, int c1, uint32_t bar) {
  asm volatile("cp.async.bulk.tensor.2d.shared::cluster.global.mbarrier::complete_tx::bytes [%0], [%1, {%3, %4}], [%2];\n" ::"r"(dst), "l"(m), "r"(bar), "r"(c0), "r"(c1) : "memory");
}
__device__ __forceinline__ void tma2d_prefetch(const CUtensorMap* m, int c0, int c1) {
  asm volatile("cp.async.bulk.prefetch.tensor.2d.L2.global [%0, {%1, %2}];\n" ::"l"(m), "r"(c0), "r"(c1) : "memory");
}
__device__ __forceinline__ void fence_async_smem() { asm volatile("fence.proxy.async.shared::cta;\n" ::: "memory"); }
__device__ __forceinline__ void bar_sync(int id, int n) { asm volatile("bar.sync %0, %1;\n" ::"r"(id), "r"(n) : "memory"); }
__device__ __forceinline__ void ldsm4(uint32_t& r0, uint32_t& r1, uint32_t& r2, uint32_t& r3, uint32_t a) {
  asm volatile("ldmatrix.sync.aligned.m8n8.x4.shared.b16 {%0,%1,%2,%3}, [%4];\n" : "=r"(r0), "=r"(r1), "=r"(r2), "=r"(r3) : "r"(a) : "memory");
}
__device__ __forceinline__ void stsm4(uint32_t a, uint32_t r0, uint32_t r1, uint32_t r2, uint32_t r3) {
  asm volatile("stmatrix.sync.aligned.m8n8.x4.shared.b16 [%0], {%1,%2,%3,%4};\n" ::"r"(a), "r"(r0), "r"(r1), "r"(r2), "r"(r3) : "memory");
}
__device__ __forceinline__ void sts128(uint32_t a, uint32_t r0, uint32_t r1, uint32_t r2, uint32_t r3) {
  asm volatile("st.shared.v4.b32 [%0], {%1,%2,%3,%4};\n" ::"r"(a), "r"(r0), "r"(r1), "r"(r2), "r"(r3) : "memory");
}
__device__ __forceinline__ void lds128(uint32_t& r0, uint32_t& r1, uint32_t& r2, uint32_t& r3, uint32_t a) {
  asm volatile("ld.shared.v4.b32 {%0,%1,%2,%3}, [%4];\n" : "=r"(r0), "=r"(r1), "=r"(r2), "=r"(r3) : "r"(a) : "memory");
}
template <int OFF>
__device__ __forceinline__ void lds128_inplace(uint32_t (&r)[4], uint32_t a) {
  asm volatile("{\n.reg .pred p;\nsetp.ne.u32 p, %4, 0;\n@p ld.shared.v4.b32 {%0,%1,%2,%3}, [%4 + %5];\n}\n"
               : "+r"(r[0]), "+r"(r[1]), "+r"(r[2]), "+r"(r[3]) : "r"(a), "n"(OFF) : "memory");
}
__device__ __forceinline__ void sts64(uint32_t a, uint32_t r0, uint32_t r1) { asm volatile("st.shared.v2.b32 [%0], {%1,%2};\n" ::"r"(a), "r"(r0), "r"(r1) : "memory"); }
__device__ __forceinline__ void lds64(uint32_t& r0, uint32_t& r1, uint32_t a) { asm volatile("ld.shared.v2.b32 {%0,%1}, [%2];\n" : "=r"(r0), "=r"(r1) : "r"(a) : "memory"); }
__device__ __forceinline__ uint32_t lds32(uint32_t a) { uint32_t v; asm volatile("ld.shared.b32 %0, [%1];\n" : "=r"(v) : "r"(a) : "memory"); return v; }
__device__ __forceinline__ void sts32(uint32_t a, uint32_t r0) { asm volatile("st.shared.b32 [%0], %1;\n" ::"r"(a), "r"(r0) : "memory"); }
__device__ __forceinline__ void mma16816(float (&c)[4], uint32_t a0, uint32_t a1, uint32_t a2, uint32_t a3, uint32_t b0, uint32_t b1) {
  asm volatile("mma.sync.aligned.m16n8k16.row.col.f32.bf16.bf16.f32 {%0,%1,%2,%3}, {%4,%5,%6,%7}, {%8,%9}, {%0,%1,%2,%3};\n"
               : "+f"(c[0]), "+f"(c[1]), "+f"(c[2]), "+f"(c[3]) : "r"(a0), "r"(a1), "r"(a2), "r"(a3), "r"(b0), "r"(b1));
}
__device__ __forceinline__ uint32_t pack2(float lo, float hi) {
  uint32_t r;
  asm("cvt.rn.bf16x2.f32 %0, %1, %2;\n" : "=r"(r) : "f"(hi), "f"(lo));
  return r;
}
__device__ __forceinline__ float blo(uint32_t w) { return __uint_as_float(w << 16); }
__device__ __forceinline__ float bhi(uint32_t w) { return __uint_as_float(w & 0xffff0000u); }
__device__ __forceinline__ float rbf(float x) { return __bfloat162float(__float2bfloat16_rn(x)); }
__device__ __forceinline__ float ex2(float x) { float r; asm("ex2.approx.ftz.f32 %0, %1;\n" : "=f"(r) : "f"(x)); return r; }
__device__ __forceinline__ float rcp(float x) { float r; asm("rcp.approx.ftz.f32 %0, %1;\n" : "=f"(r) : "f"(x)); return r; }
__device__ __forceinline__ float sqrta(float x) { float r; asm("sqrt.approx.ftz.f32 %0, %1;\n" : "=f"(r) : "f"(x)); return r; }
__device__ __forceinline__ uint32_t bsub2(uint32_t a, uint32_t b) { uint32_t r; asm("sub.rn.bf16x2 %0, %1, %2;\n" : "=r"(r) : "r"(a), "r"(b)); return r; }
__device__ __forceinline__ uint32_t ld_acq(const uint32_t* p) { uint32_t v; asm volatile("ld.acquire.gpu.global.u32 %0, [%1];\n" : "=r"(v) : "l"(p) : "memory"); return v; }
__device__ __forceinline__ void st_b128(void* p, uint32_t a, uint32_t b, uint32_t c, uint32_t d) {
  asm volatile("st.relaxed.gpu.global.v4.b32 [%0], {%1, %2, %3, %4};\n" ::"l"(p), "r"(a), "r"(b), "r"(c), "r"(d) : "memory");
}
__device__ __forceinline__ void ld_b128(uint32_t& a, uint32_t& b, uint32_t& c, uint32_t& d, const void* p) {
  asm volatile("{\n.reg .b128 v;\nld.relaxed.gpu.global.b128 v, [%4];\nmov.b128 {%0, %1, %2, %3}, v;\n}\n" : "=r"(a), "=r"(b), "=r"(c), "=r"(d) : "l"(p) : "memory");
}
__device__ __forceinline__ bool elect_one() {
  uint32_t ok;
  asm volatile("{\n.reg .pred p;\nelect.sync _|p, 0xffffffff;\nselp.u32 %0, 1, 0, p;\n}\n" : "=r"(ok));
  return ok;
}
__device__ __forceinline__ uint32_t bmul2(uint32_t a, uint32_t b) { uint32_t r; asm("mul.rn.bf16x2 %0, %1, %2;\n" : "=r"(r) : "r"(a), "r"(b)); return r; }
__device__ __forceinline__ void red_rel(uint32_t* p) { asm volatile("red.release.gpu.global.add.u32 [%0], 1;\n" ::"l"(p) : "memory"); }
__device__ __forceinline__ void wait_ge(const uint32_t* p, uint32_t target) {
  uint32_t n = 0;
  while ((int32_t)(ld_acq(p) - target) < 0) {
    __nanosleep(64);
    if (++n > SPIN_LIMIT) __trap();
  }
}
__device__ __forceinline__ float phi(float a, float r, float rl) { return fmaf(fmaxf(a, 0.f), r, __saturatef(ex2(a * rl) + 1e-6f)); }

#define ACC8(d, o) "+f"(d[o + 0]), "+f"(d[o + 1]), "+f"(d[o + 2]), "+f"(d[o + 3]), "+f"(d[o + 4]), "+f"(d[o + 5]), "+f"(d[o + 6]), "+f"(d[o + 7])
#define REGS32 "{%0,%1,%2,%3,%4,%5,%6,%7,%8,%9,%10,%11,%12,%13,%14,%15,%16,%17,%18,%19,%20,%21,%22,%23,%24,%25,%26,%27,%28,%29,%30,%31}"
__device__ __forceinline__ void wgmma_rs64(float (&d)[32], const uint32_t (&a)[4], uint64_t db, int acc) {
  asm volatile("{\n.reg .pred p;\nsetp.ne.b32 p, %37, 0;\n"
               "wgmma.mma_async.sync.aligned.m64n64k16.f32.bf16.bf16 " REGS32 ", {%32,%33,%34,%35}, %36, p, 1, 1, 1;\n}\n"
               : ACC8(d, 0), ACC8(d, 8), ACC8(d, 16), ACC8(d, 24)
               : "r"(a[0]), "r"(a[1]), "r"(a[2]), "r"(a[3]), "l"(db), "r"(acc));
}
template <uint32_t OFF, uint32_t HI>
__device__ __forceinline__ void wgmma_ss64(float (&d)[32], uint32_t da_lo, uint64_t db) {
  asm volatile("{\n.reg .b32 lo;\n.reg .b64 da;\nadd.u32 lo, %32, %34;\nmov.b64 da, {lo, %35};\n"
               "wgmma.mma_async.sync.aligned.m64n64k16.f32.bf16.bf16 " REGS32 ", da, %33, 1, 1, 1, 0, 1;\n}\n"
               : ACC8(d, 0), ACC8(d, 8), ACC8(d, 16), ACC8(d, 24)
               : "r"(da_lo), "l"(db), "n"(OFF), "n"(HI));
}
__device__ __forceinline__ void wgmma_rs24(float (&d)[12], const uint32_t (&a)[4], uint64_t db, int acc) {
  asm volatile("{\n.reg .pred p;\nsetp.ne.b32 p, %17, 0;\n"
               "wgmma.mma_async.sync.aligned.m64n24k16.f32.bf16.bf16 {%0,%1,%2,%3,%4,%5,%6,%7,%8,%9,%10,%11}, {%12,%13,%14,%15}, %16, p, 1, 1, 1;\n}\n"
               : ACC8(d, 0), "+f"(d[8]), "+f"(d[9]), "+f"(d[10]), "+f"(d[11])
               : "r"(a[0]), "r"(a[1]), "r"(a[2]), "r"(a[3]), "l"(db), "r"(acc));
}
__device__ __forceinline__ void wgmma_ss40tt(float (&d)[20], uint64_t da, uint64_t db, int acc) {
  asm volatile("{\n.reg .pred p;\nsetp.ne.b32 p, %22, 0;\n"
               "wgmma.mma_async.sync.aligned.m64n40k16.f32.bf16.bf16 {%0,%1,%2,%3,%4,%5,%6,%7,%8,%9,%10,%11,%12,%13,%14,%15,%16,%17,%18,%19}, %20, %21, p, 1, 1, 1, 1;\n}\n"
               : ACC8(d, 0), ACC8(d, 8), "+f"(d[16]), "+f"(d[17]), "+f"(d[18]), "+f"(d[19])
               : "l"(da), "l"(db), "r"(acc));
}
template <uint32_t OFF, uint32_t HI, int ACCUM>
__device__ __forceinline__ void wgmma_ss16(float (&d)[8], uint32_t da_lo, uint64_t db) {
  asm volatile("{\n.reg .b32 lo;\n.reg .b64 da;\n.reg .pred p;\nsetp.ne.b32 p, %12, 0;\nadd.u32 lo, %8, %10;\nmov.b64 da, {lo, %11};\n"
               "wgmma.mma_async.sync.aligned.m64n16k16.f32.bf16.bf16 {%0,%1,%2,%3,%4,%5,%6,%7}, da, %9, p, 1, 1, 0, 1;\n}\n"
               : ACC8(d, 0)
               : "r"(da_lo), "l"(db), "n"(OFF), "n"(HI), "n"(ACCUM));
}
template <int N> __device__ __forceinline__ void pin(float (&d)[N]) {
#pragma unroll
  for (int i = 0; i < N; i++) asm volatile("" : "+f"(d[i])::"memory");
}

__device__ __forceinline__ void pin8(float (&d)[32], const int o) { asm volatile("" : ACC8(d, o)::"memory"); }

template <int I> struct IC { static constexpr int value = I; };
template <int I, int N, class F> __device__ __forceinline__ void static_for(F f) {
  if constexpr (I < N) { f(IC<I>()); static_for<I + 1, N>(f); }
}

struct Params {
  const __nv_bfloat16* x;
  const __nv_bfloat16* wqkv;
  const __nv_bfloat16* wo;
  const __nv_bfloat16* w1;
  const __nv_bfloat16* w3;
  const __nv_bfloat16* w2;
  __nv_bfloat16* out;
};

__global__ void __launch_bounds__(NTHREADS, 1)
fused_block_kernel(const __grid_constant__ CUtensorMap m_qkv, const __grid_constant__ CUtensorMap m_w1,
                   const __grid_constant__ CUtensorMap m_w3, const __grid_constant__ CUtensorMap m_w2,
                   const __grid_constant__ CUtensorMap m_M, const __grid_constant__ CUtensorMap m_x,
                   const __grid_constant__ CUtensorMap m_l, const Params p) {
  extern __shared__ __align__(1024) uint8_t smem_raw[];
  constexpr uint32_t sb = 1024;
  if ((uint32_t)__cvta_generic_to_shared(smem_raw) != sb) __trap();
  const int tid = threadIdx.x, warp = __shfl_sync(0xffffffffu, tid >> 5, 0), lane = tid & 31;
  const int r = blockIdx.x >> 3, j = blockIdx.x & 7;

  GT(0); TSC(0);
  if (warp == 7) {
    if (elect_one()) {
#pragma unroll
      for (int b = 0; b < 9; b++) mbar_init(sb + B_X + 8 * b, 1);
      asm volatile("fence.mbarrier_init.release.cluster;\n" ::: "memory");
#pragma unroll
      for (int b = 0; b < 9; b++) {
        mbar_expect(sb + B_X + 8 * b, 16384);
        tma2d(sb + HB + b * 16384, &m_x, 64 * b, 128 * r, sb + B_X + 8 * b);
        if (b == 0) TS1(2, 20);
      }
      TS1(2, 21);
    }
    __syncwarp();
  } else if (tid < 16 * XPF) {
    asm volatile("prefetch.global.L2 [%0];\n" ::"l"(p.x + (size_t)(blockIdx.x * 16 + (tid & 15)) * D_ + (tid >> 4) * 64));
  }
  const int cmain = 72 * j + 8 * (j & 1);
  if (__builtin_expect(warp >= 8, 1)) {
    asm volatile("setmaxnreg.dec.sync.aligned.u32 24;\n");
    if (__builtin_expect(warp == 8, 1)) {
      if (elect_one()) {
        asm volatile("prefetch.tensormap [%0];\n" ::"l"(&m_qkv) : "memory");
#pragma unroll
        for (int i = 9; i < 29; i++) mbar_init(sb + BARS + 8 * i, i < 16 ? 1 : i < 26 ? 8 : i == 26 ? 4 : 96);
        asm volatile("fence.mbarrier_init.release.cluster;\n" ::: "memory");
      }
      __syncwarp();
      asm volatile("bar.sync 0, 384;\n" ::: "memory");
      if (elect_one()) {
#pragma unroll
        for (int s = 0; s < 6; s++) {
          if (s == WDELAY) mbar_wait(sb + B_X + 8 * XWAIT, 0);
          mbar_expect(sb + B_FULL + 8 * s, SLOT);
          tma2d(sb + s * SLOT, &m_qkv, D_ + cmain, 96 * s, sb + B_FULL + 8 * s);
        }
        const CUtensorMap* mpf = (r & 1) ? &m_w3 : &m_w1;
        if (r < 6) tma2d_prefetch(&m_qkv, 2 * D_ + cmain, 96 * r);
        if (r < 12) { tma2d_prefetch(mpf, 576 * j, 96 * (r >> 1)); tma2d_prefetch(mpf, 576 * j + 32, 96 * (r >> 1)); }
#pragma unroll
        for (int s = 0; s < 6; s++) {
          mbar_wait(sb + B_EMPTY + 8 * s, 0);
          mbar_expect(sb + B_FULL + 8 * s, SLOT);
          tma2d(sb + s * SLOT, &m_qkv, 2 * D_ + cmain, 96 * s, sb + B_FULL + 8 * s);
        }
#pragma unroll 1
        for (int n = 0; n < 18; n++) {
          const int col = 576 * j + 32 * n;
          if (n < 16) { if (r < 12) tma2d_prefetch(mpf, col + 64, 96 * (r >> 1)); }
          else if (r < 6) {
            if (n == 16) tma2d_prefetch(&m_qkv, cmain, 96 * r);
            else tma2d_prefetch(&m_w2, 512, 576 * j + 96 * r);
          }
#pragma unroll
          for (int s = 0; s < 6; s++) {
            mbar_wait(sb + B_EMPTY + 8 * s, (n & 1) ^ 1);
            mbar_expect(sb + B_FULL + 8 * s, SLOT);
            tma2d(sb + s * SLOT, &m_w1, col, 96 * s, sb + B_FULL + 8 * s);
            tma2d(sb + s * SLOT + SLOT / 2, &m_w3, col, 96 * s, sb + B_FULL + 8 * s);
          }
        }
        if (r < 6) tma2d_prefetch(&m_w2, 64 * ((j + 1) & 7), 576 * j + 96 * r);
#pragma unroll
        for (int s = 0; s < 6; s++) {
          mbar_wait(sb + B_EMPTY + 8 * s, 1);
          mbar_expect(sb + B_FULL + 8 * s, SLOT);
          tma2d(sb + s * SLOT, &m_qkv, cmain, 96 * s, sb + B_FULL + 8 * s);
        }
#pragma unroll 1
        for (int n = 0; n < 9; n++) {
          const int col = n == 0 ? 512 : 64 * ((j + n) & 7);
          if (n < 7 && r < 6) tma2d_prefetch(&m_w2, 64 * ((j + n + 2) & 7), 576 * j + 96 * r);
#pragma unroll
          for (int s = 0; s < 6; s++) {
            mbar_wait(sb + B_EMPTY + 8 * s, n & 1);
            mbar_expect(sb + B_FULL + 8 * s, SLOT);
            tma2d(sb + s * SLOT, &m_w2, col, 576 * j + 96 * s, sb + B_FULL + 8 * s);
          }
          if (n == 0) {
            mbar_wait(sb + B_HFREE, 0);
            mbar_wait(sb + B_MRDY, 0);
            asm volatile("fence.proxy.async;\n" ::: "memory");
          }
          mbar_wait(sb + B_EMPTY + 48, (n & 1) ^ 1);
          mbar_expect(sb + B_FULL + 48, 80 * 128);
          tma2d(sb + WO_SLOT, &m_M, col, 80 * j, sb + B_FULL + 48);
          if (n == 4) {
            mbar_expect(sb + B_X, 16384);
            tma2d(sb + XT, &m_x, 64 * j, 128 * r, sb + B_X);
          }
        }
      }
    } else {
      const int ht = tid - 288;
      asm volatile("bar.sync 0, 384;\n" ::: "memory");
      const uint32_t ep = g_epoch[blockIdx.x] + 1;
      mbar_wait(sb + B_X + 8 * 8, 0);
      if (ht < 90) {
        const int e = ht / 18, c = ht - e * 18;
        const __nv_bfloat16* w = p.wo + (size_t)(72 * j + 18 * (r >> 2) + e) * D_ + 144 * (r & 3) + c * 8;
#pragma unroll
        for (int i = 0; i < 4; i++)
          if (i < 3 || ht < 54) cp_async16(sb + WOB + ht * 16 + i * 90 * 16, w + i * 5 * D_);
      }
      const int cl = 72 * j + ((j & 1) ? 0 : 64);
      const __nv_bfloat16* wl = p.wqkv + (size_t)ht * (3 * D_) + cl;
      mbar_wait(sb + B_XDONE, 0);
      if (LTMA > 0 && warp == 11 && elect_one()) {
        asm volatile("mbarrier.expect_tx.shared::cta.b64 [%0], %1;\n" ::"r"(sb + B_LFULL), "r"(LTMA * 9216) : "memory");
#pragma unroll
        for (int m = 0; m < 3; m++)
#pragma unroll
          for (int g = 3 - LTMA; g < 3; g++) tma2d(sb + L24_T + g * 9216 + m * 3072, &m_l, cl + (g == 2 ? 0 : (g + 1) * D_), 192 * m, sb + B_LFULL);
      }
#pragma unroll
      for (int g = 0; g < 3 - LTMA; g++)
#pragma unroll
        for (int m = 0; m < 6; m++) cp_async16(sb + L24_T + g * 9216 + m * 96 * 16 + ht * 16, wl + (size_t)m * 96 * 3 * D_ + (g == 2 ? 0 : (g + 1) * D_));
      if (ht < 64) {
#pragma unroll
        for (int i = 0; i < 4; i++) sts128(sb + V_T - 2048 + (i >> 1) * 20480 + (i & 1) * 1024 + ht * 16, 0x3F803F80u, 0x3F803F80u, 0x3F803F80u, 0x3F803F80u);
      }
      asm volatile("cp.async.wait_all;\n" ::: "memory");
      fence_async_smem();
      mbar_arrive(sb + B_LFULL);
      if (warp == 9) TS(3, 1);

      if (ht == 0) {
        mbar_wait(sb + B_KVD, 0);
        red_rel(&g_cnt1[j * 32]);
        wait_ge(&g_cnt1[j * 32], 16 * ep);
      }
      bar_sync(3, 96);
      if (warp == 9) TS(3, 4);
#pragma unroll 1
      for (int i = ht; i < 171; i += 96) {
        const int dp = i / 19, el = i - dp * 19, hd = r >> 2, w = hd >> 1;
        const int d = 18 * hd + 2 * dp - 32 * w;
        const int m = el == 18 ? 56 * w : 18 * hd + el + 8 - 24 * w;
        const float2* src = reinterpret_cast<const float2*>(g_kvp + j * 16 * 1280 + ((w * 4 + (m >> 4)) * 5 + (d >> 3)) * 32 + (m & 7) * 4 + ((d & 7) >> 1)) + ((m >> 3) & 1);
        float s0 = 0.f, s1 = 0.f;
#pragma unroll 1
        for (int r4 = 0; r4 < 4; r4++) {
          const float2 v0 = __ldcg(src), v1 = __ldcg(src + 2560), v2 = __ldcg(src + 2 * 2560), v3 = __ldcg(src + 3 * 2560);
          s0 += (v0.x + v1.x) + (v2.x + v3.x);
          s1 += (v0.y + v1.y) + (v2.y + v3.y);
          src += 4 * 2560;
        }
        sts64(sb + KVS + dp * 160 + el * 8, __float_as_uint(s0), __float_as_uint(s1));
        if ((r & 3) == 0 && el == 18) *reinterpret_cast<float2*>(g_z + j * 72 + hd * 18 + dp * 2) = make_float2(s0, s1);
      }
      bar_sync(3, 96);
      if (warp == 9) TS(3, 5);
#pragma unroll 1
      for (int t = ht; t < 648; t += 96) {
        const int dp = t / 72, cp = t - dp * 72;
        float c0 = 0.f, c1 = 0.f, c2 = 0.f, c3 = 0.f;
        const uint32_t ka = sb + KVS + dp * 160, wa = sb + WOB + cp * 4;
#pragma unroll
        for (int e2 = 0; e2 < 9; e2++) {
          uint32_t a0, a1, a2, a3;
          lds128(a0, a1, a2, a3, ka + e2 * 16);
          const uint32_t w0 = lds32(wa + e2 * 576), w1 = lds32(wa + e2 * 576 + 288);
          c0 = fmaf(__uint_as_float(a0), blo(w0), c0); c1 = fmaf(__uint_as_float(a0), bhi(w0), c1);
          c2 = fmaf(__uint_as_float(a1), blo(w0), c2); c3 = fmaf(__uint_as_float(a1), bhi(w0), c3);
          c0 = fmaf(__uint_as_float(a2), blo(w1), c0); c1 = fmaf(__uint_as_float(a2), bhi(w1), c1);
          c2 = fmaf(__uint_as_float(a3), blo(w1), c2); c3 = fmaf(__uint_as_float(a3), bhi(w1), c3);
        }
        const int d = 18 * (r >> 2) + 2 * dp;
        uint32_t* dst = reinterpret_cast<uint32_t*>(g_M) + (80 * j + ((j & 1) ? (d < 8 ? d + 64 : d - 8) : d)) * 288 + 72 * (r & 3) + cp;
        dst[0] = pack2(c0, c1);
        dst[288] = pack2(c2, c3);
      }
      asm volatile("fence.proxy.async;\n" ::: "memory");
      bar_sync(3, 96);
      if (warp == 9) TS(3, 6);
      if (ht == 0) { red_rel(&g_cnt2[j * 32]); wait_ge(&g_cnt2[j * 32], 16 * ep); }
      bar_sync(3, 96);
      if (ht < 80) {
        const int d = (j & 1) ? (ht < 64 ? ht + 8 : ht - 64) : ht;
        uint32_t zb = 0;
        if (ht < 72) zb = pack2(__ldcg(g_z + j * 72 + d), 0.f);
        const int hd = d / 18;
        const uint32_t w = (hd & 1) ? zb << 16 : zb;
        const uint32_t w0 = hd < 2 ? w : 0u, w1 = hd < 2 ? 0u : w;
        sts128(sb + ZM + ht * 16, w0, w0, w0, w0);
        sts128(sb + ZM + 1280 + ht * 16, w1, w1, w1, w1);
      }
      const uint32_t tag = (ep & 1) << 16;
      if (ht == 95) { sts32(sb + TAGW, tag); g_epoch[blockIdx.x] = ep; }
      fence_async_smem();
      mbar_arrive(sb + B_MRDY);
      if (warp == 9) TS(3, 7);
      if (warp < 11) {
        mbar_wait(sb + B_FULL + 48, 0);
#pragma unroll 1
        for (int i = warp - 9; i < 4; i += 2) {
          const uint4* src = g_part + (size_t)((r * 9 + 8) * 8) * 1024 + j * 128 + i * 32 + lane;
          const int off = ((r * 128 + j * 16 + (lane >> 2)) * D_ + 512 + 16 * i + 2 * (lane & 3)) >> 1;
          float s0, s1, s2, s3, s4, s5, s6, s7;
          {
            const uint32_t* xp = reinterpret_cast<const uint32_t*>(p.x) + off;
            const uint32_t x0 = __ldg(xp), x1 = __ldg(xp + 4 * D_), x2 = __ldg(xp + 4), x3 = __ldg(xp + 4 * D_ + 4);
            s0 = blo(x0); s1 = bhi(x0); s2 = blo(x1); s3 = bhi(x1); s4 = blo(x2); s5 = bhi(x2); s6 = blo(x3); s7 = bhi(x3);
          }
          uint32_t n = 0;
#pragma unroll 1
          for (int jj = 0; jj < 8;) {
            uint32_t v0, v1, v2, v3;
            ld_b128(v0, v1, v2, v3, src);
            if (__all_sync(0xffffffffu, ((v0 ^ tag) & 0x10000u) == 0)) {
              s0 += blo(v0); s1 += __uint_as_float(v0 & 0xfffe0000u); s2 += blo(v1); s3 += bhi(v1);
              s4 += blo(v2); s5 += bhi(v2); s6 += blo(v3); s7 += bhi(v3);
              jj++;
              src += 1024;
            } else {
              __nanosleep(200);
              if (++n > SPIN_LIMIT) __trap();
            }
          }
          uint32_t* op = reinterpret_cast<uint32_t*>(p.out) + off;
          op[0] = pack2(s0, s1); op[4 * D_] = pack2(s2, s3); op[4] = pack2(s4, s5); op[4 * D_ + 4] = pack2(s6, s7);
        }
        if (warp == 9) TS(3, 10);
      }
    }
  } else {
    asm volatile("setmaxnreg.inc.sync.aligned.u32 240;\n");
    asm volatile("bar.sync 0, 384;\n" ::: "memory");
    const int wg = warp >> 2;
    uint32_t a[36][4];
    float dA[32], dB[32];
    const bool l0 = lane == 0;
    constexpr uint64_t dsw128 = mkdesc(sb, 16, 1024, 1);
    constexpr uint64_t dsw64 = mkdesc(sb, SLOT / 2, 512, 2);

    auto issue = [&](float (&d)[32], const uint64_t dbase, const int kstride, const int s, const uint32_t ph, const int init = 0) {
      mbar_wait(sb + B_FULL + 8 * s, ph);
      wg_fence();
#pragma unroll
      for (int ks = 0; ks < 6; ks++) wgmma_rs64(d, a[s * 6 + ks], dbase + ((s * SLOT + ks * kstride) >> 4), (s | ks | init) != 0);
    };
    auto finish = [&](const int rel) {
      wg_commit();
      wg_wait<1>();
      if (rel >= 0 && l0) mbar_arrive(sb + B_EMPTY + 8 * rel);
    };
    auto stW = [&](float (&d)[32], const int s, const uint32_t ph, const int rel) { issue(d, dsw128, 2048, s, ph); finish(rel); };
    auto stF = [&](float (&d)[32], const int s, const uint32_t ph, const int rel) { issue(d, dsw64, 1024, s, ph); finish(rel); };

    TSC(1);
    uint32_t mb0, mb1;
    float r0, r1;
    auto center = [&](const int g) {
#pragma unroll
      for (int ks = 6 * g; ks < 6 * g + 6; ks++) {
        a[ks][0] = bsub2(a[ks][0], mb0); a[ks][1] = bsub2(a[ks][1], mb1);
        a[ks][2] = bsub2(a[ks][2], mb0); a[ks][3] = bsub2(a[ks][3], mb1);
        asm volatile("" : "+r"(a[ks][0]), "+r"(a[ks][1]), "+r"(a[ks][2]), "+r"(a[ks][3])::"memory");
      }
    };
    {
      const uint32_t xa = sb + HB + (warp * 16 + (lane & 15)) * 128;
      const uint32_t sw = lane & 7, hi = lane >> 4;
      constexpr uint32_t ONES = 0x3F803F80u;
      float cs[2][4], cq[2][4];
#pragma unroll
      for (int i = 0; i < 4; i++) { cs[0][i] = cs[1][i] = cq[0][i] = cq[1][i] = 0.f; }
      auto rsum = [&](const int ks) { mma16816(cs[ks & 1], a[ks][0], a[ks][1], a[ks][2], a[ks][3], ONES, ONES); };
      auto rsq = [&](const int ks) {
        mma16816(cq[ks & 1], bmul2(a[ks][0], a[ks][0]), bmul2(a[ks][1], a[ks][1]), bmul2(a[ks][2], a[ks][2]), bmul2(a[ks][3], a[ks][3]), ONES, ONES);
      };
#pragma unroll
      for (int b = 0; b < 9; b++) {
        mbar_wait(sb + B_X + 8 * b, 0);
        if (b == 0 || b == 8) TSC(32 + b);
#pragma unroll
        for (int kk = 0; kk < 4; kk++) ldsm4(a[4 * b + kk][0], a[4 * b + kk][1], a[4 * b + kk][2], a[4 * b + kk][3], xa + b * 16384 + (((2 * kk + hi) ^ sw) << 4));
        if (b > 0) {
#pragma unroll
          for (int ks = 4 * b - 4; ks < 4 * b; ks++) { rsum(ks); rsq(ks); }
        }
      }
      __syncwarp();
      if (l0) mbar_arrive(sb + B_XDONE);
#pragma unroll
      for (int ks = 32; ks < 36; ks++) rsum(ks);
#pragma unroll
      for (int ks = 32; ks < 36; ks++) rsq(ks);
      TSC(2);
      const float m0 = (cs[0][0] + cs[1][0]) * (1.f / 576.f), m1 = (cs[0][2] + cs[1][2]) * (1.f / 576.f);
      mb0 = pack2(m0, m0);
      mb1 = pack2(m1, m1);
      center(0);
      TSC(3);
      stW(dA, 0, 0, -1);
      center(1);
      stW(dA, 1, 0, 0);
      const float q0 = (cq[0][0] + cq[1][0]) * (1.f / 576.f), q1 = (cq[0][2] + cq[1][2]) * (1.f / 576.f);
      float v0 = q0 - m0 * m0, v1 = q1 - m1 * m1;
      if (__any_sync(0xffffffffu, v0 < q0 * 0.5f || v1 < q1 * 0.5f)) {
        float s0 = 0.f, s1 = 0.f;
        const uint32_t* xr = reinterpret_cast<const uint32_t*>(p.x + (size_t)(r * 128 + warp * 16 + (lane >> 2)) * D_) + (lane & 3);
#pragma unroll 4
        for (int i = 0; i < 72; i++) {
          const uint32_t e0 = __ldg(xr + 4 * i), e1 = __ldg(xr + 4 * D_ + 4 * i);
          float t;
          t = blo(e0) - m0; s0 = fmaf(t, t, s0); t = bhi(e0) - m0; s0 = fmaf(t, t, s0);
          t = blo(e1) - m1; s1 = fmaf(t, t, s1); t = bhi(e1) - m1; s1 = fmaf(t, t, s1);
        }
        s0 += __shfl_xor_sync(0xffffffffu, s0, 1); s1 += __shfl_xor_sync(0xffffffffu, s1, 1);
        s0 += __shfl_xor_sync(0xffffffffu, s0, 2); s1 += __shfl_xor_sync(0xffffffffu, s1, 2);
        v0 = s0 * (1.f / 576.f); v1 = s1 * (1.f / 576.f);
      }
      r0 = rcp(rbf(sqrta(rbf(rbf(fmaxf(v0, 0.f)) + 1e-5f))));
      r1 = rcp(rbf(sqrta(rbf(rbf(fmaxf(v1, 0.f)) + 1e-5f))));
    }
#pragma unroll
    for (int s = 2; s < 6; s++) {
      center(s);
      stW(dA, s, 0, s - 1);
    }
    TSC(4); GT(1);
    constexpr float LOG2E = 1.4426950408889634f;
    float l0e = r0 * LOG2E, l1e = r1 * LOG2E;
    const uint32_t tile_off = ((lane >> 4) + (j & 1)) * 2048 + (warp * 16 + (lane & 15)) * 16;
    mbar_wait(sb + B_XDONE, 0);
#pragma unroll
    for (int s = 0; s < 6; s++) {
      stW(dB, s, 1, (s + 5) % 6);
      TSC(50 + s);
      if (s < 4) {
        const int t = 2 * s;
        pin8(dA, 4 * t);
        stsm4(sb + PK_T + tile_off + t * 2048, pack2(phi(dA[4 * t], r0, l0e), phi(dA[4 * t + 1], r0, l0e)), pack2(phi(dA[4 * t + 2], r1, l1e), phi(dA[4 * t + 3], r1, l1e)),
              pack2(phi(dA[4 * t + 4], r0, l0e), phi(dA[4 * t + 5], r0, l0e)), pack2(phi(dA[4 * t + 6], r1, l1e), phi(dA[4 * t + 7], r1, l1e)));
      }
    }
    TSC(5);
    {
#pragma unroll
      for (int s = 0; s < 2; s++) {
        stF(dA, s, 0, (s + 5) % 6);
#pragma unroll
        for (int t = 4 * s; t < 4 * s + 4; t += 2) {
          pin8(dB, 4 * t);
          stsm4(sb + V_T + tile_off + t * 2048, pack2(dB[4 * t] * r0, dB[4 * t + 1] * r0), pack2(dB[4 * t + 2] * r1, dB[4 * t + 3] * r1),
                pack2(dB[4 * t + 4] * r0, dB[4 * t + 5] * r0), pack2(dB[4 * t + 6] * r1, dB[4 * t + 7] * r1));
        }
      }
      float dL[12];
      constexpr uint64_t dl = mkdesc(sb + L24_T, 128, 576 * 16, 0);
      mbar_wait(sb + B_LFULL, 0);
#pragma unroll
      for (int s = 2; s < 5; s++) {
        mbar_wait(sb + B_FULL + 8 * s, 0);
        wg_fence();
#pragma unroll
        for (int ks = 12 * (s - 2); ks < 12 * (s - 1); ks++) wgmma_rs24(dL, a[ks], dl + ks * 16, ks != 0);
#pragma unroll
        for (int ks = 0; ks < 6; ks++) wgmma_rs64(dA, a[s * 6 + ks], dsw64 + ((s * SLOT + ks * 1024) >> 4), 1);
        finish(s - 1);
      }
      stF(dA, 5, 0, 4);
      pin(dL);
      const uint32_t lo = ((j & 1) ? 0 : 8 * 2048) + warp * 256 + lane * 4;
      sts32(sb + PK_T + lo, pack2(phi(dL[0], r0, l0e), phi(dL[1], r0, l0e)));
      sts32(sb + PK_T + lo + 128, pack2(phi(dL[2], r1, l1e), phi(dL[3], r1, l1e)));
      sts32(sb + V_T + lo, pack2(dL[4] * r0, dL[5] * r0));
      sts32(sb + V_T + lo + 128, pack2(dL[6] * r1, dL[7] * r1));
      sts64(sb + Q8 + tid * 8, pack2(dL[8], dL[9]), pack2(dL[10], dL[11]));
      fence_async_smem();
      __syncwarp();
      if (l0) mbar_arrive(sb + B_KVT);
    }
    TSC(6);
    uint32_t hs = sb + HB + wg * HHALF + (tid & 127) * 16;
    uint32_t hp0, hp1;
    const float iq0 = rcp(r0 * r0), iq1 = rcp(r1 * r1);
    auto epiF = [&](float (&d)[32], const int pc) {
      asm volatile("" : "+f"(d[4 * pc]), "+f"(d[4 * pc + 1]), "+f"(d[4 * pc + 2]), "+f"(d[4 * pc + 3]), "+f"(d[4 * pc + 16]), "+f"(d[4 * pc + 17]),
                   "+f"(d[4 * pc + 18]), "+f"(d[4 * pc + 19])::"memory");
      const float g0 = d[4 * pc], g1 = d[4 * pc + 1], g2 = d[4 * pc + 2], g3 = d[4 * pc + 3];
      const uint32_t h0 = pack2(g0 * d[4 * pc + 16] * rcp(fmaf(ex2(-g0 * l0e), iq0, iq0)), g1 * d[4 * pc + 17] * rcp(fmaf(ex2(-g1 * l0e), iq0, iq0)));
      const uint32_t h1 = pack2(g2 * d[4 * pc + 18] * rcp(fmaf(ex2(-g2 * l1e), iq1, iq1)), g3 * d[4 * pc + 19] * rcp(fmaf(ex2(-g3 * l1e), iq1, iq1)));
      if (pc & 1) {
        sts128(hs, hp0, hp1, h0, h1);
        hs += 2048;
      } else {
        hp0 = h0; hp1 = h1;
        asm volatile("" : "+r"(hp0), "+r"(hp1)::"memory");
      }
    };
    {
      stF(dB, 0, 1, 5);
      epiF(dA, 0); epiF(dA, 1);
      stF(dB, 1, 1, 0);
      epiF(dA, 2); epiF(dA, 3);
      float dK[20];
      const uint64_t ka = mkdesc(sb + V_T - 2048 + wg * 3 * 2048, 128, 2048, 0), kb = mkdesc(sb + PK_T + wg * 4 * 2048, 128, 2048, 0);
      mbar_wait(sb + B_KVT, 0);
      mbar_wait(sb + B_FULL + 8 * 2, 1);
      wg_fence();
#pragma unroll
      for (int ks = 0; ks < 8; ks++) wgmma_ss40tt(dK, ka + ks * 16, kb + ks * 16, ks != 0);
#pragma unroll
      for (int ks = 0; ks < 6; ks++) wgmma_rs64(dB, a[12 + ks], dsw64 + ((2 * SLOT + ks * 1024) >> 4), 1);
      finish(1);
      stF(dB, 3, 1, 2);
      pin(dK);
      float4* dst = g_kvp + (j * 16 + r) * 1280 + warp * 160 + lane;
#pragma unroll
      for (int t = 0; t < 5; t++) __stcg(dst + t * 32, make_float4(dK[4 * t], dK[4 * t + 1], dK[4 * t + 2], dK[4 * t + 3]));
      __syncwarp();
      if (l0) mbar_arrive(sb + B_KVD);
      stF(dB, 4, 1, 3);
    }
#pragma unroll 1
    for (int it = 0; it < 8; it++) {
      stF(dB, 5, 1, 4);
      stF(dA, 0, 0, 5);
#pragma unroll
      for (int s = 1; s < 5; s++) { epiF(dB, s - 1); stF(dA, s, 0, s - 1); }
      stF(dA, 5, 0, 4);
      stF(dB, 0, 1, 5);
#pragma unroll
      for (int s = 1; s < 5; s++) { epiF(dA, s - 1); stF(dB, s, 1, s - 1); }
      TSC(7 + it);
    }
    stF(dB, 5, 1, 4);
    TSC(15);
    const uint32_t hl = sb + HB + wg * HHALF + (tid & 127) * 16;
    auto reload = [&](auto k0, auto k1) {
      static_for<decltype(k0)::value, decltype(k1)::value>([&](auto k) { lds128_inplace<decltype(k)::value * 2048>(a[decltype(k)::value], hl); });
    };
    stW(dA, 0, 0, 5);
    epiF(dB, 0);
    stW(dA, 1, 0, 0);
    reload(IC<0>(), IC<4>());
    epiF(dB, 1);
    stW(dA, 2, 0, 1);
    reload(IC<4>(), IC<8>());
    epiF(dB, 2);
    stW(dA, 3, 0, 2);
    reload(IC<8>(), IC<12>());
    __syncwarp();
    if (l0 && wg == 0) mbar_arrive(sb + B_HFREE);
    epiF(dB, 3);
    stW(dA, 4, 0, 3);
    reload(IC<12>(), IC<17>());
    stW(dA, 5, 0, 4);
    reload(IC<17>(), IC<22>());
    const uint32_t ot = sb + HB + wg * HHALF;
    const uint32_t do_a = (uint32_t)mkdesc(ot, 128, 1280, 0);
    constexpr uint64_t do_b = mkdesc(sb + WO_SLOT, 16, 1024, 1);
    auto stO = [&](float (&d)[32], const uint32_t ph, const int rel) {
      mbar_wait(sb + B_FULL + 48, ph);
      wg_fence();
      wgmma_ss64<0, 80>(d, do_a, do_b);
      wgmma_ss64<16, 80>(d, do_a, do_b + 128);
      wgmma_ss64<32, 80>(d, do_a, do_b + 256);
      wgmma_ss64<48, 80>(d, do_a, do_b + 384);
      wgmma_ss64<64, 80>(d, do_a, do_b + 512);
      finish(rel);
    };
    uint32_t tag;
    auto epiP = [&](float (&d)[32], const int step) {
      pin(d);
      const int c = step == 0 ? 8 : ((j + step) & 7);
      uint4* dst = g_part + (size_t)((r * 9 + c) * 8 + j) * 1024 + warp * 128 + lane;
#pragma unroll
      for (int i = 0; i < 4; i++)
        st_b128(dst + i * 32, (pack2(d[8 * i], d[8 * i + 1]) & 0xfffeffffu) | tag, pack2(d[8 * i + 2], d[8 * i + 3]), pack2(d[8 * i + 4], d[8 * i + 5]), pack2(d[8 * i + 6], d[8 * i + 7]));
    };
    TSC(16);
    {
      stW(dB, 0, 1, 5);
      reload(IC<22>(), IC<26>());
      asm volatile("" : "+f"(l0e), "+f"(l1e));
      r0 = l0e * (1.f / LOG2E); r1 = l1e * (1.f / LOG2E);
      uint32_t pq[18];
      const uint32_t oa = ot + ((warp & 3) * 2 + ((lane >> 3) & 1)) * 1280 + (lane >> 4) * 128 + (lane & 7) * 16;
      auto phiq = [&](const int t0, const int t1) {
#pragma unroll
        for (int t = t0; t < t1; t++) {
          asm volatile("" : "+f"(dA[4 * t]), "+f"(dA[4 * t + 1]), "+f"(dA[4 * t + 2]), "+f"(dA[4 * t + 3])::"memory");
          pq[2 * t] = pack2(phi(dA[4 * t], r0, l0e), phi(dA[4 * t + 1], r0, l0e));
          pq[2 * t + 1] = pack2(phi(dA[4 * t + 2], r1, l1e), phi(dA[4 * t + 3], r1, l1e));
          asm volatile("" : "+r"(pq[2 * t]), "+r"(pq[2 * t + 1])::"memory");
        }
      };
      phiq(0, 3);
      bar_sync(1 + wg, 128);
      stW(dB, 1, 1, 0);
      reload(IC<26>(), IC<30>());
      phiq(3, 6);
      stW(dB, 2, 1, 1);
      phiq(6, 8);
      {
        uint32_t q0, q1;
        lds64(q0, q1, sb + Q8 + tid * 8);
        pq[16] = pack2(phi(blo(q0), r0, l0e), phi(bhi(q0), r0, l0e));
        pq[17] = pack2(phi(blo(q1), r1, l1e), phi(bhi(q1), r1, l1e));
      }
#pragma unroll
      for (int t = 0; t < 8; t += 2) stsm4(oa + t * 128, pq[2 * t], pq[2 * t + 1], pq[2 * t + 2], pq[2 * t + 3]);
      stsm4(oa + 1024, pq[16], pq[17], 0u, 0u);
      fence_async_smem();
      TSC(17);
      mbar_wait(sb + B_MRDY, 0);
      TSC(18);
      tag = lds32(sb + TAGW);
      float den[8];
      constexpr uint64_t dz = mkdesc(sb + ZM, 128, 1280, 0);
      bar_sync(1 + wg, 128);
      issue(dB, dsw128, 2048, 3, 1);
      wgmma_ss16<0, 80, 0>(den, do_a, dz);
      wgmma_ss16<16, 80, 1>(den, do_a, dz + 16);
      wgmma_ss16<32, 80, 1>(den, do_a, dz + 32);
      wgmma_ss16<48, 80, 1>(den, do_a, dz + 48);
      wgmma_ss16<64, 80, 1>(den, do_a, dz + 64);
      finish(2);
      reload(IC<30>(), IC<36>());
      stW(dB, 4, 1, 3);
      pin(den);
      uint32_t iv[8];
#pragma unroll
      for (int i = 0; i < 8; i++) { const float t = rcp(den[i] + 1e-6f); iv[i] = pack2(t, t); }
      const int u = 2 * (lane & 3) + 8 * (j & 1);
#pragma unroll
      for (int t = 0; t < 10; t += 2) {
        uint32_t o[4];
#pragma unroll
        for (int z = 0; z < 2; z++) {
          const int tt = t + z;
          if (tt < 9) {
            const int lo = tt == 0 ? 0 : tt >= 7 ? 3 : (tt - 1) >> 1, hi = tt == 8 ? 0 : (tt == 0 || tt == 7) ? lo : lo + 1;
            const bool up = tt == 8 ? (j & 1) : 8 * tt + u >= 18 * hi;
            const int il = (lo >> 1) * 4 + (lo & 1), ih = (hi >> 1) * 4 + (hi & 1);
            o[2 * z] = bmul2(pq[2 * tt], up ? iv[ih] : iv[il]);
            o[2 * z + 1] = bmul2(pq[2 * tt + 1], up ? iv[ih + 2] : iv[il + 2]);
          } else {
            o[2 * z] = 0; o[2 * z + 1] = 0;
          }
        }
        stsm4(oa + t * 128, o[0], o[1], o[2], o[3]);
      }
      fence_async_smem();
      stW(dB, 5, 1, 4);
      bar_sync(1 + wg, 128);
      stO(dB, 0, 5);
    }
    stW(dA, 0, 0, 6);
    epiP(dB, 0);
    TSC(19);
    auto ldp = [&](uint32_t (&v)[16], const int c, const int dj) {
      const uint4* src = g_part + (size_t)((r * 9 + c) * 8 + ((j + dj) & 7)) * 1024 + warp * 128 + lane;
#pragma unroll
      for (int i = 0; i < 4; i++) ld_b128(v[4 * i], v[4 * i + 1], v[4 * i + 2], v[4 * i + 3], src + i * 32);
    };
    auto chk = [&](uint32_t (&v)[16], const int c, const int dj) {
      uint32_t n = 0;
      while (__any_sync(0xffffffffu, (((v[0] ^ tag) | (v[4] ^ tag) | (v[8] ^ tag) | (v[12] ^ tag)) & 0x10000u) != 0)) {
        ldp(v, c, dj);
        if (++n > SPIN_LIMIT) asm volatile("trap;");
      }
    };
    auto unp = [&](float (&d)[32], uint32_t (&v)[16], const int i) {
      d[8 * i] = blo(v[4 * i]); d[8 * i + 1] = __uint_as_float(v[4 * i] & 0xfffe0000u); d[8 * i + 2] = blo(v[4 * i + 1]); d[8 * i + 3] = bhi(v[4 * i + 1]);
      d[8 * i + 4] = blo(v[4 * i + 2]); d[8 * i + 5] = bhi(v[4 * i + 2]); d[8 * i + 6] = blo(v[4 * i + 3]); d[8 * i + 7] = bhi(v[4 * i + 3]);
      pin8(d, 8 * i);
    };
#pragma unroll
    for (int s = 1; s < 6; s++) stW(dA, s, 0, s - 1);
    stO(dA, 1, 5);
    stW(dB, 0, 1, 6);
    epiP(dA, 1);
    TSC(20);
#pragma unroll 1
    for (int it = 0; it < 3; it++) {
      uint32_t v[16];
      stW(dB, 1, 1, 0);
#pragma unroll
      for (int i = 0; i < 16; i++) v[i] = (i & 3) ? 0u : tag;
      if (it > 0) ldp(v, (j + 3 + 2 * it) & 7, 3);
      stW(dB, 2, 1, 1);
      stW(dB, 3, 1, 2);
      stW(dB, 4, 1, 3);
      chk(v, (j + 3 + 2 * it) & 7, 3);
      unp(dA, v, 0); unp(dA, v, 1);
      stW(dB, 5, 1, 4);
      unp(dA, v, 2); unp(dA, v, 3);
      stO(dB, 0, 5);
      issue(dA, dsw128, 2048, 0, 0, 1); finish(6);
      epiP(dB, 2 + 2 * it);
      stW(dA, 1, 0, 0);
      ldp(v, (j + 4 + 2 * it) & 7, 3);
      stW(dA, 2, 0, 1);
      stW(dA, 3, 0, 2);
      stW(dA, 4, 0, 3);
      chk(v, (j + 4 + 2 * it) & 7, 3);
      unp(dB, v, 0); unp(dB, v, 1);
      stW(dA, 5, 0, 4);
      unp(dB, v, 2); unp(dB, v, 3);
      stO(dA, 1, 5);
      issue(dB, dsw128, 2048, 0, 1, 1); finish(6);
      epiP(dA, 3 + 2 * it);
      TSC(21 + it);
    }
    {
      uint32_t v[16], w[16], xv[16];
      float f[32] = {};
      auto addv = [&](uint32_t (&v)[16], const int i) {
        f[8 * i] += blo(v[4 * i]); f[8 * i + 1] += __uint_as_float(v[4 * i] & 0xfffe0000u); f[8 * i + 2] += blo(v[4 * i + 1]); f[8 * i + 3] += bhi(v[4 * i + 1]);
        f[8 * i + 4] += blo(v[4 * i + 2]); f[8 * i + 5] += bhi(v[4 * i + 2]); f[8 * i + 6] += blo(v[4 * i + 3]); f[8 * i + 7] += bhi(v[4 * i + 3]);
        pin8(f, 8 * i);
      };
      ldp(v, j, 2);
      mbar_wait(sb + B_X, 1);
#pragma unroll
      for (int i = 0; i < 4; i++)
        ldsm4(xv[4 * i], xv[4 * i + 1], xv[4 * i + 2], xv[4 * i + 3], sb + XT + (warp * 16 + (lane & 15)) * 128 + (((2 * i + (lane >> 4)) ^ (lane & 7)) << 4));
      stW(dB, 1, 1, -1);
      TSC(44);
#pragma unroll
      for (int i = 0; i < 16; i++) { f[2 * i] = blo(xv[i]); f[2 * i + 1] = bhi(xv[i]); }
      pin(f);
      stW(dB, 2, 1, -1);
      TSC(45);
      chk(v, j, 2);
      addv(v, 0); addv(v, 1);
      stW(dB, 3, 1, -1);
      TSC(46);
      addv(v, 2); addv(v, 3);
      ldp(w, j, 1);
      stW(dB, 4, 1, -1);
      TSC(47);
      stW(dB, 5, 1, -1);
      TSC(48);
      chk(w, j, 1);
      TSC(49);
      addv(w, 0); addv(w, 1);
      stO(dB, 0, -1);
      TSC(24);
      addv(w, 2); addv(w, 3);
      TSC(25);
      wg_wait<0>();
      TSC(26); GT(2);
      pin(dB);
      const uint32_t ps = sb + HB + wg * HHALF + STG + (warp & 3) * 2048;
      const int row = lane & 15;
#pragma unroll
      for (int t = 0; t < 8; t += 2)
        stsm4(ps + row * 128 + (((t + (lane >> 4)) ^ (row & 7)) << 4),
              pack2(f[4 * t] + dB[4 * t], f[4 * t + 1] + dB[4 * t + 1]), pack2(f[4 * t + 2] + dB[4 * t + 2], f[4 * t + 3] + dB[4 * t + 3]),
              pack2(f[4 * t + 4] + dB[4 * t + 4], f[4 * t + 5] + dB[4 * t + 5]), pack2(f[4 * t + 6] + dB[4 * t + 6], f[4 * t + 7] + dB[4 * t + 7]));
      __syncwarp();
      TSC(56);
#pragma unroll
      for (int i = 0; i < 4; i++) {
        const int rr = i * 4 + (lane >> 3), ch = lane & 7;
        uint4 o;
        lds128(o.x, o.y, o.z, o.w, ps + rr * 128 + ((ch ^ (rr & 7)) << 4));
        *reinterpret_cast<uint4*>(p.out + (size_t)(r * 128 + warp * 16 + rr) * D_ + 64 * j + ch * 8) = o;
      }
    }
    TSC(27); GT(3);
  }
}

typedef CUresult (*EncodeFn)(CUtensorMap*, CUtensorMapDataType, cuuint32_t, void*, const cuuint64_t*, const cuuint64_t*, const cuuint32_t*,
                             const cuuint32_t*, CUtensorMapInterleave, CUtensorMapSwizzle, CUtensorMapL2promotion, CUtensorMapFloatOOBfill);

CUtensorMap make_map(EncodeFn enc, const void* ptr, int rows, int cols, int brow, int bcol, CUtensorMapSwizzle sw) {
  CUtensorMap m;
  cuuint64_t gd[2] = {(cuuint64_t)cols, (cuuint64_t)rows};
  cuuint64_t gs[1] = {(cuuint64_t)cols * 2};
  cuuint32_t bd[2] = {(cuuint32_t)bcol, (cuuint32_t)brow};
  cuuint32_t es[2] = {1, 1};
  enc(&m, CU_TENSOR_MAP_DATA_TYPE_BFLOAT16, 2, const_cast<void*>(ptr), gd, gs, bd, es, CU_TENSOR_MAP_INTERLEAVE_NONE, sw,
      CU_TENSOR_MAP_L2_PROMOTION_L2_128B, CU_TENSOR_MAP_FLOAT_OOB_FILL_NONE);
  return m;
}

}

extern "C" void kernel_launch(void* const* d_in, const int* in_sizes, int n_in, void* d_out, int out_size) {
  (void)in_sizes; (void)n_in; (void)out_size;
  static EncodeFn enc = nullptr;
  static void* m_ptr = nullptr;
  if (!enc) {
    cudaGetSymbolAddress(&m_ptr, g_M);
    cudaDriverEntryPointQueryResult qr;
    cudaGetDriverEntryPoint("cuTensorMapEncodeTiled", (void**)&enc, cudaEnableDefault, &qr);
    cudaFuncSetAttribute(fused_block_kernel, cudaFuncAttributeMaxDynamicSharedMemorySize, SMEM_BYTES);
  }
  Params p;
  p.x = (const __nv_bfloat16*)d_in[0];
  p.wqkv = (const __nv_bfloat16*)d_in[1];
  p.wo = (const __nv_bfloat16*)d_in[2];
  p.w1 = (const __nv_bfloat16*)d_in[4];
  p.w3 = (const __nv_bfloat16*)d_in[5];
  p.w2 = (const __nv_bfloat16*)d_in[6];
  p.out = (__nv_bfloat16*)d_out;
  const CUtensorMap m_qkv = make_map(enc, p.wqkv, D_, 3 * D_, 96, 64, CU_TENSOR_MAP_SWIZZLE_128B);
  const CUtensorMap m_w1 = make_map(enc, p.w1, D_, F_, 96, 32, CU_TENSOR_MAP_SWIZZLE_64B);
  const CUtensorMap m_w3 = make_map(enc, p.w3, D_, F_, 96, 32, CU_TENSOR_MAP_SWIZZLE_64B);
  const CUtensorMap m_w2 = make_map(enc, p.w2, F_, D_, 96, 64, CU_TENSOR_MAP_SWIZZLE_128B);
  const CUtensorMap m_M = make_map(enc, m_ptr, 8 * 80, D_, 80, 64, CU_TENSOR_MAP_SWIZZLE_128B);
  const CUtensorMap m_x = make_map(enc, p.x, 2048, D_, 128, 64, CU_TENSOR_MAP_SWIZZLE_128B);
  const CUtensorMap m_l = make_map(enc, p.wqkv, D_, 3 * D_, 192, 8, CU_TENSOR_MAP_SWIZZLE_NONE);
  fused_block_kernel<<<128, NTHREADS, SMEM_BYTES>>>(m_qkv, m_w1, m_w3, m_w2, m_M, m_x, m_l, p);
}
```

```cpp
#include <cuda_runtime.h>
#include <cuda.h>
#include <cuda_bf16.h>
#include <stdint.h>

namespace {

constexpr int D_ = 576, F_ = 4608;
constexpr int NTHREADS = 384;

constexpr uint32_t SLOT = 12288;
constexpr uint32_t HB = 6 * SLOT;
constexpr uint32_t HHALF = 73728;
constexpr uint32_t PK_T = HB + 45056;
constexpr uint32_t V_T = HB + HHALF + 18432;
constexpr uint32_t L24_T = HB + 16384;
constexpr uint32_t WO_SLOT = HB + 12288;
constexpr uint32_t XT = HB + 24576;
constexpr uint32_t STG = 49152;
constexpr uint32_t Q8 = HB + 2 * HHALF;
constexpr uint32_t ZM = Q8 + 2048;
constexpr uint32_t TAGW = ZM + 2560;
constexpr uint32_t BARS = TAGW + 32;
constexpr uint32_t SMEM_BYTES = BARS + 256;

constexpr uint32_t B_X = BARS;
constexpr uint32_t B_FULL = BARS + 8 * 9;
constexpr uint32_t B_EMPTY = BARS + 8 * 16;
constexpr uint32_t B_XDONE = BARS + 8 * 23;
constexpr uint32_t B_KVT = BARS + 8 * 24;
constexpr uint32_t B_KVD = BARS + 8 * 25;
constexpr uint32_t B_DONE = BARS + 8 * 26;
constexpr uint32_t B_LFULL = BARS + 8 * 27;
constexpr uint32_t B_MRDY = BARS + 8 * 28;

constexpr int XPF = 4;
constexpr int LW = 4;
constexpr int PFW = 8;
constexpr int PFS = 2;
constexpr int XWAIT = 0;
constexpr uint32_t SPIN_LIMIT = 1u << 20;

__device__ __align__(512) uint4 g_part[16 * 9 * 8 * 1024];
__device__ float4 g_kvp[8 * 16 * 1280];
__device__ __align__(128) __nv_bfloat16 g_M[8 * 80 * 576];
__device__ __align__(16) float g_z[8 * 72];
__device__ __align__(128) uint4 g_L[8 * 1728];
__device__ uint32_t g_cnt0[8 * 32], g_cnt1[8 * 32], g_cnt2[8 * 32];
__device__ uint32_t g_epoch[128], g_epoch2[4];

__device__ __forceinline__ void wg_fence() { asm volatile("wgmma.fence.sync.aligned;\n" ::: "memory"); }
__device__ __forceinline__ void wg_commit() { asm volatile("wgmma.commit_group.sync.aligned;\n" ::: "memory"); }
template <int N> __device__ __forceinline__ void wg_wait() { asm volatile("wgmma.wait_group.sync.aligned %0;\n" ::"n"(N) : "memory"); }
__host__ __device__ constexpr uint64_t mkdesc(uint32_t addr, uint32_t lbo, uint32_t sbo, uint32_t sw) {
  return (uint64_t)((addr & 0x3FFFF) >> 4) | ((uint64_t)(lbo >> 4) << 16) | ((uint64_t)(sbo >> 4) << 32) | ((uint64_t)sw << 62);
}
__device__ __forceinline__ void mbar_init(uint32_t a, uint32_t c) { asm volatile("mbarrier.init.shared::cta.b64 [%0], %1;\n" ::"r"(a), "r"(c) : "memory"); }
__device__ __forceinline__ void mbar_arrive(uint32_t a) { asm volatile("mbarrier.arrive.shared::cta.b64 _, [%0];\n" ::"r"(a) : "memory"); }
__device__ __forceinline__ void mbar_wait(uint32_t a, uint32_t ph) {
  asm volatile(
      "{\n.reg .pred p;\n.reg .u32 n;\n"
      "mov.u32 n, 0;\n"
      "LOOP:\n"
      "mbarrier.try_wait.parity.shared::cta.b64 p, [%0], %1;\n"
      "@p bra DONE;\n"
      "add.u32 n, n, 1;\n"
      "setp.gt.u32 p, n, %2;\n"
      "@p trap;\n"
      "bra LOOP;\n"
      "DONE:\n}\n" ::"r"(a), "r"(ph), "n"(SPIN_LIMIT) : "memory");
}
__device__ __forceinline__ void mbar_spin(uint32_t a, uint32_t ph) {
  asm volatile("{\n.reg .pred p;\nLOOP:\nbar.warp.sync 0xffffffff;\nmbarrier.try_wait.parity.shared::cta.b64 p, [%0], %1;\n@!p bra LOOP;\n}\n" ::"r"(a), "r"(ph) : "memory");
}
__device__ __forceinline__ bool mbar_test(uint32_t a, uint32_t ph) {
  uint32_t ok;
  asm volatile("{\n.reg .pred p;\nmbarrier.test_wait.parity.shared::cta.b64 p, [%1], %2;\nselp.u32 %0, 1, 0, p;\n}\n" : "=r"(ok) : "r"(a), "r"(ph) : "memory");
  return ok;
}
__device__ __forceinline__ void cp_async16(uint32_t dst, const void* src) {
  asm volatile("cp.async.cg.shared.global [%0], [%1], 16;\n" ::"r"(dst), "l"(src) : "memory");
}
__device__ __forceinline__ void tma2d_elect(uint32_t dst, const CUtensorMap* m, int c0, int c1, uint32_t bar, uint32_t bytes) {
  asm volatile("{\n.reg .pred p;\nelect.sync _|p, 0xffffffff;\n"
               "@p mbarrier.arrive.expect_tx.shared::cta.b64 _, [%2], %5;\n"
               "@p cp.async.bulk.tensor.2d.shared::cluster.global.mbarrier::complete_tx::bytes [%0], [%1, {%3, %4}], [%2];\n}\n"
               ::"r"(dst), "l"(m), "r"(bar), "r"(c0), "r"(c1), "r"(bytes) : "memory");
}
__device__ __forceinline__ void tma2d_elect2(uint32_t dst, const CUtensorMap* m, int c0, int c1, uint32_t bar) {
  asm volatile("{\n.reg .pred p;\nelect.sync _|p, 0xffffffff;\n"
               "@p cp.async.bulk.tensor.2d.shared::cluster.global.mbarrier::complete_tx::bytes [%0], [%1, {%3, %4}], [%2];\n}\n"
               ::"r"(dst), "l"(m), "r"(bar), "r"(c0), "r"(c1) : "memory");
}
__device__ __forceinline__ void tma2d_prefetch(const CUtensorMap* m, int c0, int c1) {
  asm volatile("{\n.reg .pred p;\nelect.sync _|p, 0xffffffff;\n@p cp.async.bulk.prefetch.tensor.2d.L2.global [%0, {%1, %2}];\n}\n" ::"l"(m), "r"(c0), "r"(c1) : "memory");
}
__device__ __forceinline__ void fence_async_smem() { asm volatile("fence.proxy.async.shared::cta;\n" ::: "memory"); }
__device__ __forceinline__ void bar_sync(int id, int n) { asm volatile("bar.sync %0, %1;\n" ::"r"(id), "r"(n) : "memory"); }
__device__ __forceinline__ void ldsm4(uint32_t& r0, uint32_t& r1, uint32_t& r2, uint32_t& r3, uint32_t a) {
  asm volatile("ldmatrix.sync.aligned.m8n8.x4.shared.b16 {%0,%1,%2,%3}, [%4];\n" : "=r"(r0), "=r"(r1), "=r"(r2), "=r"(r3) : "r"(a) : "memory");
}
__device__ __forceinline__ void stsm4(uint32_t a, uint32_t r0, uint32_t r1, uint32_t r2, uint32_t r3) {
  asm volatile("stmatrix.sync.aligned.m8n8.x4.shared.b16 [%0], {%1,%2,%3,%4};\n" ::"r"(a), "r"(r0), "r"(r1), "r"(r2), "r"(r3) : "memory");
}
__device__ __forceinline__ void sts128(uint32_t a, uint32_t r0, uint32_t r1, uint32_t r2, uint32_t r3) {
  asm volatile("st.shared.v4.b32 [%0], {%1,%2,%3,%4};\n" ::"r"(a), "r"(r0), "r"(r1), "r"(r2), "r"(r3) : "memory");
}
__device__ __forceinline__ void lds128(uint32_t& r0, uint32_t& r1, uint32_t& r2, uint32_t& r3, uint32_t a) {
  asm volatile("ld.shared.v4.b32 {%0,%1,%2,%3}, [%4];\n" : "=r"(r0), "=r"(r1), "=r"(r2), "=r"(r3) : "r"(a) : "memory");
}
template <int OFF>
__device__ __forceinline__ void lds128_inplace(uint32_t (&r)[4], uint32_t a) {
  asm volatile("{\n.reg .pred p;\nsetp.ne.u32 p, %4, 0;\n@p ld.shared.v4.b32 {%0,%1,%2,%3}, [%4 + %5];\n}\n"
               : "+r"(r[0]), "+r"(r[1]), "+r"(r[2]), "+r"(r[3]) : "r"(a), "n"(OFF) : "memory");
}
__device__ __forceinline__ void mov_inplace(uint32_t& r, uint32_t v, uint32_t nonzero) {
  asm volatile("{\n.reg .pred p;\nsetp.ne.u32 p, %2, 0;\n@p mov.b32 %0, %1;\n}\n" : "+r"(r) : "r"(v), "r"(nonzero));
}
__device__ __forceinline__ void sts64(uint32_t a, uint32_t r0, uint32_t r1) { asm volatile("st.shared.v2.b32 [%0], {%1,%2};\n" ::"r"(a), "r"(r0), "r"(r1) : "memory"); }
__device__ __forceinline__ void lds64(uint32_t& r0, uint32_t& r1, uint32_t a) { asm volatile("ld.shared.v2.b32 {%0,%1}, [%2];\n" : "=r"(r0), "=r"(r1) : "r"(a) : "memory"); }
__device__ __forceinline__ uint32_t lds32(uint32_t a) { uint32_t v; asm volatile("ld.shared.b32 %0, [%1];\n" : "=r"(v) : "r"(a) : "memory"); return v; }
__device__ __forceinline__ void sts32(uint32_t a, uint32_t r0) { asm volatile("st.shared.b32 [%0], %1;\n" ::"r"(a), "r"(r0) : "memory"); }
__device__ __forceinline__ void mma16816(float (&c)[4], uint32_t a0, uint32_t a1, uint32_t a2, uint32_t a3, uint32_t b0, uint32_t b1) {
  asm volatile("mma.sync.aligned.m16n8k16.row.col.f32.bf16.bf16.f32 {%0,%1,%2,%3}, {%4,%5,%6,%7}, {%8,%9}, {%0,%1,%2,%3};\n"
               : "+f"(c[0]), "+f"(c[1]), "+f"(c[2]), "+f"(c[3]) : "r"(a0), "r"(a1), "r"(a2), "r"(a3), "r"(b0), "r"(b1));
}
__device__ __forceinline__ uint32_t pack2(float lo, float hi) {
  uint32_t r;
  asm("cvt.rn.bf16x2.f32 %0, %1, %2;\n" : "=r"(r) : "f"(hi), "f"(lo));
  return r;
}
__device__ __forceinline__ float blo(uint32_t w) { return __uint_as_float(w << 16); }
__device__ __forceinline__ float bhi(uint32_t w) { return __uint_as_float(w & 0xffff0000u); }
__device__ __forceinline__ float rbf(float x) { return __bfloat162float(__float2bfloat16_rn(x)); }
__device__ __forceinline__ float ex2(float x) { float r; asm("ex2.approx.ftz.f32 %0, %1;\n" : "=f"(r) : "f"(x)); return r; }
__device__ __forceinline__ float rcp(float x) { float r; asm("rcp.approx.ftz.f32 %0, %1;\n" : "=f"(r) : "f"(x)); return r; }
__device__ __forceinline__ float sqrta(float x) { float r; asm("sqrt.approx.ftz.f32 %0, %1;\n" : "=f"(r) : "f"(x)); return r; }
__device__ __forceinline__ uint32_t bsub2(uint32_t a, uint32_t b) { uint32_t r; asm("sub.rn.bf16x2 %0, %1, %2;\n" : "=r"(r) : "r"(a), "r"(b)); return r; }
__device__ __forceinline__ uint32_t ld_acq(const uint32_t* p) { uint32_t v; asm volatile("ld.acquire.gpu.global.u32 %0, [%1];\n" : "=r"(v) : "l"(p) : "memory"); return v; }
__device__ __forceinline__ void st_b128(void* p, uint32_t a, uint32_t b, uint32_t c, uint32_t d) {
  asm volatile("st.relaxed.gpu.global.v4.b32 [%0], {%1, %2, %3, %4};\n" ::"l"(p), "r"(a), "r"(b), "r"(c), "r"(d) : "memory");
}
__device__ __forceinline__ void ld_b128(uint32_t& a, uint32_t& b, uint32_t& c, uint32_t& d, const void* p) {
  asm volatile("ld.relaxed.gpu.global.v4.b32 {%0, %1, %2, %3}, [%4];\n" : "=r"(a), "=r"(b), "=r"(c), "=r"(d) : "l"(p) : "memory");
}
__device__ __forceinline__ bool elect_one() {
  uint32_t ok;
  asm volatile("{\n.reg .pred p;\nelect.sync _|p, 0xffffffff;\nselp.u32 %0, 1, 0, p;\n}\n" : "=r"(ok));
  return ok;
}
__device__ __forceinline__ uint32_t bfma2(uint32_t a, uint32_t b, uint32_t c) { uint32_t r; asm("fma.rn.bf16x2 %0, %1, %2, %3;\n" : "=r"(r) : "r"(a), "r"(b), "r"(c)); return r; }
__device__ __forceinline__ uint32_t bmul2(uint32_t a, uint32_t b) { uint32_t r; asm("mul.rn.bf16x2 %0, %1, %2;\n" : "=r"(r) : "r"(a), "r"(b)); return r; }
__device__ __forceinline__ void red_rel(uint32_t* p) { asm volatile("red.release.gpu.global.add.u32 [%0], 1;\n" ::"l"(p) : "memory"); }
__device__ __forceinline__ void wait_ge(const uint32_t* p, uint32_t target, const uint32_t sleep = 200) {
  uint32_t n = 0;
  while ((int32_t)(ld_acq(p) - target) < 0) {
    if (sleep) __nanosleep(sleep);
    if (++n > SPIN_LIMIT) __trap();
  }
}
__device__ __forceinline__ float phi(float a, float r, float rl) { return fmaf(fmaxf(a, 0.f), r, __saturatef(ex2(a * rl) + 1e-6f)); }

#define ACC8(d, o) "+f"(d[o + 0]), "+f"(d[o + 1]), "+f"(d[o + 2]), "+f"(d[o + 3]), "+f"(d[o + 4]), "+f"(d[o + 5]), "+f"(d[o + 6]), "+f"(d[o + 7])
#define REGS32 "{%0,%1,%2,%3,%4,%5,%6,%7,%8,%9,%10,%11,%12,%13,%14,%15,%16,%17,%18,%19,%20,%21,%22,%23,%24,%25,%26,%27,%28,%29,%30,%31}"
__device__ __forceinline__ void wgmma_rs64(float (&d)[32], const uint32_t (&a)[4], uint64_t& db, int64_t inc, int acc) {
  asm volatile("{\n.reg .pred p;\nsetp.ne.b32 p, %37, 0;\nadd.s64 %32, %32, %38;\n"
               "wgmma.mma_async.sync.aligned.m64n64k16.f32.bf16.bf16 " REGS32 ", {%33,%34,%35,%36}, %32, p, 1, 1, 1;\n}\n"
               : ACC8(d, 0), ACC8(d, 8), ACC8(d, 16), ACC8(d, 24), "+l"(db)
               : "r"(a[0]), "r"(a[1]), "r"(a[2]), "r"(a[3]), "r"(acc), "l"(inc));
}
__device__ __forceinline__ void wgmma_ss64(float (&d)[32], uint64_t& da, int64_t inca, uint64_t& db, int64_t incb) {
  asm volatile("add.s64 %32, %32, %34;\nadd.s64 %33, %33, %35;\n"
               "wgmma.mma_async.sync.aligned.m64n64k16.f32.bf16.bf16 " REGS32 ", %32, %33, 1, 1, 1, 0, 1;\n"
               : ACC8(d, 0), ACC8(d, 8), ACC8(d, 16), ACC8(d, 24), "+l"(da), "+l"(db)
               : "l"(inca), "l"(incb));
}
__device__ __forceinline__ void wgmma_rs24(float (&d)[12], const uint32_t (&a)[4], uint64_t db, int acc) {
  asm volatile("{\n.reg .pred p;\nsetp.ne.b32 p, %17, 0;\n"
               "wgmma.mma_async.sync.aligned.m64n24k16.f32.bf16.bf16 {%0,%1,%2,%3,%4,%5,%6,%7,%8,%9,%10,%11}, {%12,%13,%14,%15}, %16, p, 1, 1, 1;\n}\n"
               : ACC8(d, 0), "+f"(d[8]), "+f"(d[9]), "+f"(d[10]), "+f"(d[11])
               : "r"(a[0]), "r"(a[1]), "r"(a[2]), "r"(a[3]), "l"(db), "r"(acc));
}
__device__ __forceinline__ void wgmma_ss40tt(float (&d)[20], uint64_t da, uint64_t db, int acc) {
  asm volatile("{\n.reg .pred p;\nsetp.ne.b32 p, %22, 0;\n"
               "wgmma.mma_async.sync.aligned.m64n40k16.f32.bf16.bf16 {%0,%1,%2,%3,%4,%5,%6,%7,%8,%9,%10,%11,%12,%13,%14,%15,%16,%17,%18,%19}, %20, %21, p, 1, 1, 1, 1;\n}\n"
               : ACC8(d, 0), ACC8(d, 8), "+f"(d[16]), "+f"(d[17]), "+f"(d[18]), "+f"(d[19])
               : "l"(da), "l"(db), "r"(acc));
}
__device__ __forceinline__ void wgmma_rs16(float (&d)[8], const uint32_t (&a)[4], uint64_t db, int acc) {
  asm volatile("{\n.reg .pred p;\nsetp.ne.b32 p, %13, 0;\n"
               "wgmma.mma_async.sync.aligned.m64n16k16.f32.bf16.bf16 {%0,%1,%2,%3,%4,%5,%6,%7}, {%8,%9,%10,%11}, %12, p, 1, 1, 1;\n}\n"
               : ACC8(d, 0)
               : "r"(a[0]), "r"(a[1]), "r"(a[2]), "r"(a[3]), "l"(db), "r"(acc));
}
template <int N> __device__ __forceinline__ void pin(float (&d)[N]) {
#pragma unroll
  for (int i = 0; i < N; i++) asm volatile("" : "+f"(d[i])::"memory");
}

__device__ __forceinline__ void pin8(float (&d)[32], const int o) { asm volatile("" : ACC8(d, o)::"memory"); }

template <int I> struct IC { static constexpr int value = I; };
template <int I, int N, class F> __device__ __forceinline__ void static_for(F f) {
  if constexpr (I < N) { f(IC<I>()); static_for<I + 1, N>(f); }
}

struct Params {
  const __nv_bfloat16* x;
  uint64_t d0[2];
  int64_t back[2];
  uint64_t dl, dz, dob;
  int64_t backa, backb;
  __nv_bfloat16* out;
  const __nv_bfloat16* wqkv;
  const __nv_bfloat16* wo;
};
__host__ __device__ constexpr uint64_t ring_desc(int sw64, int k) {
  return sw64 ? mkdesc(1024 + (k / 6) * SLOT + (k % 6) * 1024, SLOT / 2, 512, 2) : mkdesc(1024 + (k / 6) * SLOT + (k % 6) * 2048, 16, 1024, 1);
}
#define DESC(sw64, k) rd[sw64], ((k) == 0 ? p.back[sw64] : (int64_t)(ring_desc(sw64, k) - ring_desc(sw64, (k) ? (k) - 1 : 0)))

__device__ __forceinline__ void side_cta(const Params& p, const uint32_t sb) {
  constexpr uint32_t WP = 1168, WO = 0, KV = 144 * WP;
  const int tid = threadIdx.x, j0 = 2 * (blockIdx.x - 128);
  __nanosleep(5000);
  const uint32_t ep = g_epoch2[blockIdx.x - 128] + 1;
  for (int i = tid; i < 144 * 72; i += NTHREADS) cp_async16(sb + WO + i * 16 + (i / 72) * 16, p.wo + (size_t)j0 * 72 * D_ + i * 8);
  for (int i = tid; i < 8 * 160; i += NTHREADS) sts128(sb + KV + i * 16, 0, 0, 0, 0);
  for (int i = tid; i < 2 * 576; i += NTHREADS) reinterpret_cast<uint4*>(g_M)[(80 * (j0 + i / 576) + 72) * 72 + i % 576] = make_uint4(0, 0, 0, 0);
  if (tid < 2) wait_ge(&g_cnt1[(j0 + tid) * 32], 16 * ep);
  __syncthreads();
  if (tid == 0) g_epoch2[blockIdx.x - 128] = ep;
  {
    const int wi = tid >> 5, lane = tid & 31, jj = wi / 6, aw = wi - jj * 6, w = aw / 3, cw = w * 4 + aw - 2 * w;
#pragma unroll 1
    for (int t = 0; t < 5; t++) {
      const float4* src = g_kvp + (j0 + jj) * 16 * 1280 + (cw * 5 + t) * 32 + lane;
      float4 v[16];
#pragma unroll
      for (int rr = 0; rr < 16; rr++) v[rr] = __ldcg(src + rr * 1280);
      float s[4] = {0.f, 0.f, 0.f, 0.f};
#pragma unroll
      for (int rr = 0; rr < 16; rr++) { s[0] += v[rr].x; s[1] += v[rr].y; s[2] += v[rr].z; s[3] += v[rr].w; }
      const int d = 8 * t + 2 * (lane & 3) + 32 * w, hd = d / 18;
#pragma unroll
      for (int h = 0; h < 2; h++) {
        const int m = (cw & 3) * 16 + 8 * h + (lane >> 2);
        const int el = m == 56 * w ? 18 : m - 8 + 24 * w - 18 * hd;
        const bool ones = (m >> 3) == 7 * w;
        if ((hd >> 1) == w && (ones ? m == 56 * w : (el >= 0 && el < 18))) {
          if (ones) *reinterpret_cast<float2*>(g_z + (j0 + jj) * 72 + d) = make_float2(s[2 * h], s[2 * h + 1]);
          else {
            const uint32_t ka = sb + KV + (jj * 4 + hd) * 2560 + (d - 18 * hd) * 80 + el * 2, kw = pack2(s[2 * h], s[2 * h + 1]);
            asm volatile("st.shared.u16 [%0], %1;\nst.shared.u16 [%0 + 80], %2;\n" ::"r"(ka), "h"((uint16_t)kw), "h"((uint16_t)(kw >> 16)) : "memory");
          }
        }
      }
    }
  }
  asm volatile("cp.async.wait_all;\n" ::: "memory");
  __syncthreads();
  {
    const int lane = tid & 31;
#pragma unroll 1
    for (int u = (tid >> 5) * 2; u < (tid >> 5) * 2 + 2; u++) {
      const int h8 = u / 3;
      uint32_t a[4][4];
#pragma unroll
      for (int i = 0; i < 4; i++)
        ldsm4(a[i][0], a[i][1], a[i][2], a[i][3], sb + KV + h8 * 2560 + ((i >> 1) * 16 + (lane & 15)) * 80 + (i & 1) * 32 + (lane >> 4) * 16);
      const uint32_t base = sb + WO + h8 * 18 * WP + (u - h8 * 3) * 384;
#pragma unroll 4
      for (int t = 0; t < 24; t++) {
        uint32_t b0, b1, b2, b3;
        asm volatile("ldmatrix.sync.aligned.m8n8.x4.trans.shared.b16 {%0,%1,%2,%3}, [%4];\n" : "=r"(b0), "=r"(b1), "=r"(b2), "=r"(b3) : "r"(base + min(lane, 17) * WP + t * 16) : "memory");
        float c0[4] = {}, c1[4] = {};
        mma16816(c0, a[0][0], a[0][1], a[0][2], a[0][3], b0, b1);
        mma16816(c1, a[2][0], a[2][1], a[2][2], a[2][3], b0, b1);
        mma16816(c0, a[1][0], a[1][1], a[1][2], a[1][3], b2, b3);
        mma16816(c1, a[3][0], a[3][1], a[3][2], a[3][3], b2, b3);
        const uint32_t oa = base + (lane >> 2) * WP + t * 16 + (lane & 3) * 4;
        sts32(oa, pack2(c0[0], c0[1]));
        sts32(oa + 8 * WP, pack2(c0[2], c0[3]));
        if (lane < 8) sts32(oa + 16 * WP, pack2(c1[0], c1[1]));
      }
    }
  }
  __syncthreads();
#pragma unroll 3
  for (int i = tid; i < 144 * 72; i += NTHREADS) {
    const int row = i / 72, j = j0 + row / 72, d = row % 72;
    uint4 q;
    lds128(q.x, q.y, q.z, q.w, sb + WO + i * 16 + row * 16);
    reinterpret_cast<uint4*>(g_M)[(80 * j + ((j & 1) ? (d < 8 ? d + 64 : d - 8) : d)) * 72 + i - row * 72] = q;
  }
  asm volatile("fence.proxy.async;\n" ::: "memory");
  __syncthreads();
  if (tid < 2) red_rel(&g_cnt2[(j0 + tid) * 32]);
}

__global__ void __launch_bounds__(NTHREADS, 1)
fused_block_kernel(const Params p, const __grid_constant__ CUtensorMap m_x, const __grid_constant__ CUtensorMap m_qkv, const __grid_constant__ CUtensorMap m_w1,
                   const __grid_constant__ CUtensorMap m_w3, const __grid_constant__ CUtensorMap m_w2,
                   const __grid_constant__ CUtensorMap m_M) {
  extern __shared__ __align__(1024) uint8_t smem_raw[];
  constexpr uint32_t sb = 1024;
  const int tid = threadIdx.x, warp = __shfl_sync(0xffffffffu, tid >> 5, 0), lane = tid & 31;
  const int r = blockIdx.x >> 3, j = blockIdx.x & 7;
  if (warp + (r & 16) == 7) {
    if (elect_one()) {
#pragma unroll
      for (int b = 0; b < 9; b++) mbar_init(sb + B_X + 8 * b, 1);
      asm volatile("fence.mbarrier_init.release.cluster;\n" ::: "memory");
    }
    __syncwarp();
#pragma unroll 1
    for (int b = 0; b < 9; b++) tma2d_elect(sb + HB + b * 16384, &m_x, 64 * b, 128 * r, sb + B_X + 8 * b, 16384);
  } else if (tid + (r & 16) * 16 < 16 * XPF) {
    asm volatile("prefetch.global.L2 [%0];\n" ::"l"(p.x + (size_t)(blockIdx.x * 16 + (tid & 15)) * D_ + (tid >> 4) * 64));
  }
  if (r == 16) { side_cta(p, sb); return; }
  const int cmain = 72 * j + 8 * (j & 1);
  if (warp >= 8) {
    asm volatile("setmaxnreg.dec.sync.aligned.u32 24;\n");
    if (__shfl_sync(0xffffffffu, tid, 0) >= 288) {
      asm volatile("barrier.sync 1, 384;\n" ::: "memory");
      if (warp == 9) {
        if ((uint32_t)__cvta_generic_to_shared(smem_raw) != sb) __trap();
        if (lane == 0) {
          asm volatile("prefetch.tensormap [%0];\n" ::"l"(&m_w1) : "memory");
          asm volatile("prefetch.tensormap [%0];\n" ::"l"(&m_w3) : "memory");
        }
        mbar_wait(sb + B_X + 8 * PFW, 0);
        if (r < 6) tma2d_prefetch(&m_qkv, 2 * D_ + cmain, 96 * r);
#pragma unroll 1
        for (int q = 2; q < 30; q++) {
          const bool pf = q < 20;
          const CUtensorMap* pm = pf ? ((r & 1) ? &m_w3 : &m_w1) : q == 20 ? &m_qkv : &m_w2;
          const int pc = pf ? 576 * j + (q == 19 ? 0 : 32 * (q - 1)) : q == 20 ? cmain : q == 21 ? 512 : 64 * ((j + q - 21) & 7);
          const int pr = pf ? 96 * (r >> 1) : (q == 20 ? 0 : 576 * j) + 96 * r;
          mbar_wait(sb + B_FULL + 8 * PFS, q & 1);
          if (r < (pf ? 12 : 6)) tma2d_prefetch(pm, pc, pr);
          if (q == 18 && lane == 0) {
            asm volatile("prefetch.tensormap [%0];\n" ::"l"(&m_w2) : "memory");
            asm volatile("prefetch.tensormap [%0];\n" ::"l"(&m_M) : "memory");
          }
        }
        return;
      }
      const int ht = tid - 320;
      uint32_t ep = g_epoch[blockIdx.x];
      {
        const int k = ht / 3, g = ht - k * 3;
        const uint4* src = reinterpret_cast<const uint4*>(p.wqkv + (size_t)(36 * r) * (3 * D_) + 72 * j + ((j & 1) ? 0 : 64)) + ht * 72;
        uint4* dst = g_L + j * 1728 + 36 * r + (g == 0 ? 2 : g - 1) * 576 + k;
        mbar_wait(sb + B_X + 8 * LW, 0);
        if (ht < 54) {
          const uint4 v0 = __ldg(src), v1 = __ldg(src + 54 * 72);
          dst[0] = v0; dst[18] = v1;
        }
        ep = __shfl_sync(0xffffffffu, ep + 1, 0);
        bar_sync(3, 64);
        if (ht == 0) g_epoch[blockIdx.x] = ep;
        if (ht == 32) {
          red_rel(&g_cnt0[j * 32]);
          wait_ge(&g_cnt0[j * 32], 16 * ep, 0);
          mbar_wait(sb + B_XDONE, 0);
          asm volatile("fence.proxy.async.global;\n"
                       "mbarrier.expect_tx.shared::cta.b64 [%2], 27648;\n"
                       "cp.async.bulk.shared::cluster.global.mbarrier::complete_tx::bytes [%0], [%1], 27648, [%2];\n"
                       ::"r"(sb + L24_T), "l"(g_L + j * 1728), "r"(sb + B_LFULL) : "memory");
        }
      }
      mbar_wait(sb + B_XDONE, 0);
      if (ht < 32) {
#pragma unroll
        for (int i = 0; i < 8; i++) sts128(sb + V_T - 2048 + (i >> 2) * 20480 + (i & 3) * 512 + ht * 16, 0x3F803F80u, 0x3F803F80u, 0x3F803F80u, 0x3F803F80u);
        fence_async_smem();
      }
      mbar_arrive(sb + B_LFULL);
      if (ht == 0) {
        mbar_wait(sb + B_KVD, 0);
        red_rel(&g_cnt1[j * 32]);
        __nanosleep(5000);
        wait_ge(&g_cnt2[j * 32], ep);
      }
      bar_sync(3, 64);
#pragma unroll 1
      for (int i = ht; i < 80; i += 64) {
        const int d = (j & 1) ? (i < 64 ? i + 8 : i - 64) : i;
        uint32_t zb = 0;
        if (i < 72) zb = pack2(__ldcg(g_z + j * 72 + d), 0.f);
        const int hd = d / 18;
        const uint32_t w = (hd & 1) ? zb << 16 : zb;
        const uint32_t w0 = hd < 2 ? w : 0u, w1 = hd < 2 ? 0u : w;
        sts128(sb + ZM + i * 16, w0, w0, w0, w0);
        sts128(sb + ZM + 1280 + i * 16, w1, w1, w1, w1);
      }
      const uint32_t tag = (ep & 1) << 16;
      if (ht == 63) sts32(sb + TAGW, tag);
      asm volatile("fence.proxy.async;\n" ::: "memory");
      mbar_arrive(sb + B_MRDY);
      {
        mbar_wait(sb + B_FULL + 48, 0);
        mbar_wait(sb + B_FULL + 48, 1);
        __nanosleep(600);
#pragma unroll 1
        for (int i = warp - 10; i < 4; i += 2) {
          const uint4* src = g_part + (size_t)((r * 9 + 8) * 8) * 1024 + j * 128 + i * 32 + lane;
          float s0 = 0.f, s1 = 0.f, s2 = 0.f, s3 = 0.f, s4 = 0.f, s5 = 0.f, s6 = 0.f, s7 = 0.f;
          uint32_t n = 0;
#pragma unroll 1
          for (int jj = 0; jj < 8;) {
            uint32_t v0, v1, v2, v3;
            ld_b128(v0, v1, v2, v3, src);
            if (__all_sync(0xffffffffu, ((v0 ^ tag) & 0x10000u) == 0)) {
              s0 += blo(v0); s1 += __uint_as_float(v0 & 0xfffe0000u); s2 += blo(v1); s3 += bhi(v1);
              s4 += blo(v2); s5 += bhi(v2); s6 += blo(v3); s7 += bhi(v3);
              jj++;
              src += 1024;
            } else {
              __nanosleep(200);
              if (++n > SPIN_LIMIT) __trap();
            }
          }
          const uint32_t ln = ((uint32_t)(size_t)src >> 4) & 31;
          const int off = ((r * 128 + j * 16 + (ln >> 2)) * D_ + 512 + 16 * i + 2 * (ln & 3)) >> 1;
          const uint32_t* xp = reinterpret_cast<const uint32_t*>(p.x) + off;
          const uint32_t x0 = __ldg(xp), x1 = __ldg(xp + 4 * D_), x2 = __ldg(xp + 4), x3 = __ldg(xp + 4 * D_ + 4);
          uint32_t* op = reinterpret_cast<uint32_t*>(p.out) + off;
          op[0] = pack2(s0 + blo(x0), s1 + bhi(x0)); op[4 * D_] = pack2(s2 + blo(x1), s3 + bhi(x1));
          op[4] = pack2(s4 + blo(x2), s5 + bhi(x2)); op[4 * D_ + 4] = pack2(s6 + blo(x3), s7 + bhi(x3));
        }
      }
    } else {
      if (elect_one()) {
        asm volatile("prefetch.tensormap [%0];\n" ::"l"(&m_qkv) : "memory");
#pragma unroll
        for (int i = 9; i < 29; i++) mbar_init(sb + BARS + 8 * i, i < 16 ? 1 : i < 27 ? 8 : 64);
        asm volatile("fence.mbarrier_init.release.cluster;\n" ::: "memory");
      }
      __syncwarp();
      asm volatile("barrier.sync 1, 384;\n" ::: "memory");
#pragma unroll 1
      for (int n = 0; n < 30; n++) {
        const bool ffn = n >= 2 && n < 20, down = n > 20;
        const CUtensorMap* m = ffn ? &m_w1 : down ? &m_w2 : &m_qkv;
        const int col = ffn ? 576 * j + (n == 19 ? 0 : 32 * (n - 1)) : down ? (n == 21 ? 512 : 64 * ((j + n - 21) & 7)) : (n == 20 ? 0 : (n + 1) * D_) + cmain;
        int row = down ? 576 * j : 0;
        uint32_t dst = sb, bar = sb + B_FULL;
#pragma unroll 1
        for (int s2 = 0; s2 < 3; s2++) {
#pragma unroll
          for (int z = 0; z < 2; z++) {
            mbar_wait(bar + (B_EMPTY - B_FULL) + 8 * z, (n & 1) ^ 1);
            tma2d_elect(dst + z * SLOT, m, col, row + 96 * z, bar + 8 * z, SLOT);
            if (ffn) tma2d_elect2(dst + z * SLOT + SLOT / 2, &m_w3, col, row + 96 * z, bar + 8 * z);
          }
          if (n == 0) mbar_wait(sb + B_X + 8 * XWAIT, 0);
          dst += 2 * SLOT; bar += 16; row += 192;
        }
        if (down) {
          if (n == 21) mbar_wait(sb + B_MRDY, 0);
          mbar_wait(sb + B_EMPTY + 48, n & 1);
          tma2d_elect(sb + WO_SLOT, &m_M, col, 80 * j, sb + B_FULL + 48, 80 * 128);
          if (n == 23 + (j & 3)) tma2d_elect(sb + XT, &m_x, 64 * j, 128 * r, sb + B_X, 16384);
        }
      }
      mbar_wait(sb + B_DONE, 0);
    }
  } else {
    asm volatile("setmaxnreg.inc.sync.aligned.u32 240;\n");
    asm volatile("barrier.sync 1, 384;\n" ::: "memory");
    const int wg = warp >> 2;
    uint32_t a[36][4];
    float dA[32], dB[32];
    const bool l0 = lane == 0;
    uint64_t rd[2] = {p.d0[0], p.d0[1]};

    auto mm0 = [&](float (&d)[32], const int sw64, const int s, const int init = 0) {
#pragma unroll
      for (int ks = 0; ks < 6; ks++) wgmma_rs64(d, a[s * 6 + ks], DESC(sw64, s * 6 + ks), (s | ks | init) != 0);
      wg_commit();
    };
    auto mm = [&](float (&d)[32], const int sw64, const int s, const int init = 0) { wg_fence(); mm0(d, sw64, s, init); };
    auto fin = [&](const int next, const uint32_t ph, const int rel) {
      mbar_spin(sb + B_FULL + 8 * next, ph);
      wg_wait<1>();
      if (rel >= 0 && l0) mbar_arrive(sb + B_EMPTY + 8 * rel);
    };
    auto fin1 = [&](const int s, const uint32_t ph) { fin((s + 1) % 6, s == 5 ? ph ^ 1 : ph, (s + 5) % 6); };
    auto pinr = [&](uint32_t (&o)[4]) { asm volatile("" : "+r"(o[0]), "+r"(o[1]), "+r"(o[2]), "+r"(o[3])::"memory"); };

    uint32_t mb0, mb1;
    float r0, r1;
    auto center = [&](const int g) {
#pragma unroll
      for (int ks = 6 * g; ks < 6 * g + 6; ks++) {
        a[ks][0] = bsub2(a[ks][0], mb0); a[ks][1] = bsub2(a[ks][1], mb1);
        a[ks][2] = bsub2(a[ks][2], mb0); a[ks][3] = bsub2(a[ks][3], mb1);
        pinr(a[ks]);
      }
    };
    {
      uint32_t xa[4];
#pragma unroll
      for (int kk = 0; kk < 4; kk++) xa[kk] = __shfl_sync(0xffffffffu, sb + HB + (warp * 16 + (lane & 15)) * 128 + (((2 * kk + (lane >> 4)) ^ (lane & 7)) << 4), lane);
      const uint32_t ONES = __shfl_sync(0xffffffffu, 0x3F803F80u, lane), ONES2 = __shfl_sync(0xffffffffu, 0x3F803F80u, lane ^ 1);
      float cs[2][4], cq[4];
#pragma unroll
      for (int i = 0; i < 4; i++) { cs[0][i] = cs[1][i] = cq[i] = 0.f; }
      mma16816(cq, 0u, 0u, 0u, 0u, ONES, ONES2);
      auto rsum = [&](const int ks) { mma16816(cs[ks & 1], a[ks][0], a[ks][1], a[ks][2], a[ks][3], ONES, ONES2); };
      auto rsq = [&](const int b) {
        uint32_t t[4];
#pragma unroll
        for (int i = 0; i < 4; i++) {
          t[i] = bmul2(a[4 * b][i], a[4 * b][i]);
#pragma unroll
          for (int kk = 1; kk < 4; kk++) t[i] = bfma2(a[4 * b + kk][i], a[4 * b + kk][i], t[i]);
        }
        mma16816(cq, t[0], t[1], t[2], t[3], ONES, ONES2);
      };
      bool ready = false;
#pragma unroll
      for (int b = 0; b < 9; b++) {
        if (!ready) mbar_spin(sb + B_X + 8 * b, 0);
        ready = mbar_test(sb + B_X + 8 * b + 8, 0);
#pragma unroll
        for (int kk = 0; kk < 4; kk++) ldsm4(a[4 * b + kk][0], a[4 * b + kk][1], a[4 * b + kk][2], a[4 * b + kk][3], xa[kk] + b * 16384);
        if (b > 0) {
#pragma unroll
          for (int ks = 4 * b - 4; ks < 4 * b; ks++) rsum(ks);
          rsq(b - 1);
        }
      }
      __syncwarp();
      if (l0) mbar_arrive(sb + B_XDONE);
#pragma unroll
      for (int ks = 32; ks < 36; ks++) rsum(ks);
      rsq(8);
      if (!ready) mbar_spin(sb + B_FULL, 0);
      const float m0 = (cs[0][0] + cs[1][0]) * (1.f / 576.f), m1 = (cs[0][2] + cs[1][2]) * (1.f / 576.f);
      mb0 = pack2(m0, m0);
      mb1 = pack2(m1, m1);
      center(0);
#pragma unroll
      for (int s = 0; s < 5; s++) { mm(dA, 0, s); center(s + 1); fin(s + 1, 0, s - 1); }
      mm(dA, 0, 5);
      const float q0 = cq[0] * (1.f / 576.f), q1 = cq[2] * (1.f / 576.f);
      float v0 = q0 - m0 * m0, v1 = q1 - m1 * m1;
      if (__builtin_expect(__any_sync(0xffffffffu, v0 < q0 * 0.2f || v1 < q1 * 0.2f), 0)) {
        float s0 = 0.f, s1 = 0.f;
        const uint4* xr = reinterpret_cast<const uint4*>(p.x + (size_t)(r * 128 + warp * 16 + (lane >> 2)) * D_) + (lane & 3);
#pragma unroll 1
        for (int i = 0; i < 18; i++) {
          const uint4 e0 = __ldg(xr + 4 * i), e1 = __ldg(xr + D_ + 4 * i);
          const uint32_t w0[4] = {e0.x, e0.y, e0.z, e0.w}, w1[4] = {e1.x, e1.y, e1.z, e1.w};
#pragma unroll
          for (int z = 0; z < 4; z++) {
            float t;
            t = blo(w0[z]) - m0; s0 = fmaf(t, t, s0); t = bhi(w0[z]) - m0; s0 = fmaf(t, t, s0);
            t = blo(w1[z]) - m1; s1 = fmaf(t, t, s1); t = bhi(w1[z]) - m1; s1 = fmaf(t, t, s1);
          }
        }
        s0 += __shfl_xor_sync(0xffffffffu, s0, 1); s1 += __shfl_xor_sync(0xffffffffu, s1, 1);
        s0 += __shfl_xor_sync(0xffffffffu, s0, 2); s1 += __shfl_xor_sync(0xffffffffu, s1, 2);
        v0 = s0 * (1.f / 576.f); v1 = s1 * (1.f / 576.f);
      }
      fin1(5, 0);
      mm(dB, 0, 0);
      r0 = rcp(rbf(sqrta(rbf(rbf(fmaxf(v0, 0.f)) + 1e-5f))));
      r1 = rcp(rbf(sqrta(rbf(rbf(fmaxf(v1, 0.f)) + 1e-5f))));
    }
    constexpr float LOG2E = 1.4426950408889634f;
    float l0e = r0 * LOG2E, l1e = r1 * LOG2E;
    uint32_t tile_off = ((lane >> 4) + (j & 1)) * 2048 + (warp * 16 + (lane & 15)) * 16;
    asm volatile("" : "+f"(r0), "+f"(r1), "+f"(l0e), "+f"(l1e), "+r"(tile_off)::"memory");
    mbar_spin(sb + B_XDONE, 0);
    fin1(0, 1);
#pragma unroll
    for (int s = 1; s < 6; s++) {
      mm(dB, 0, s);
      uint32_t o[4];
      const int t = 2 * s - 2;
      if (s < 5) {
        pin8(dA, 4 * t);
        o[0] = pack2(phi(dA[4 * t], r0, l0e), phi(dA[4 * t + 1], r0, l0e)); o[1] = pack2(phi(dA[4 * t + 2], r1, l1e), phi(dA[4 * t + 3], r1, l1e));
        o[2] = pack2(phi(dA[4 * t + 4], r0, l0e), phi(dA[4 * t + 5], r0, l0e)); o[3] = pack2(phi(dA[4 * t + 6], r1, l1e), phi(dA[4 * t + 7], r1, l1e));
        pinr(o);
      }
      fin1(s, 1);
      if (s < 5) stsm4(sb + PK_T + tile_off + t * 2048, o[0], o[1], o[2], o[3]);
    }
    {
      mm(dA, 1, 0);
      fin1(0, 0);
#pragma unroll
      for (int s = 1; s < 3; s++) {
        mm(dA, 1, s);
        uint32_t o[2][4];
#pragma unroll
        for (int z = 0; z < 2; z++) {
          const int t = 4 * s - 4 + 2 * z;
          pin8(dB, 4 * t);
          o[z][0] = pack2(dB[4 * t] * r0, dB[4 * t + 1] * r0); o[z][1] = pack2(dB[4 * t + 2] * r1, dB[4 * t + 3] * r1);
          o[z][2] = pack2(dB[4 * t + 4] * r0, dB[4 * t + 5] * r0); o[z][3] = pack2(dB[4 * t + 6] * r1, dB[4 * t + 7] * r1);
          pinr(o[z]);
        }
        fin1(s, 0);
#pragma unroll
        for (int z = 0; z < 2; z++) stsm4(sb + V_T + tile_off + (4 * s - 4 + 2 * z) * 2048, o[z][0], o[z][1], o[z][2], o[z][3]);
      }
      float dL[12];
      const uint64_t dl = p.dl;
      mm(dA, 1, 3);
      mbar_spin(sb + B_LFULL, 0);
      fin1(3, 0);
      wg_fence();
#pragma unroll
      for (int ks = 0; ks < 36; ks++) wgmma_rs24(dL, a[ks], dl + ks * 16, ks != 0);
      wg_commit();
      mm0(dA, 1, 4);
      fin1(4, 0);
      mm(dA, 1, 5);
      pin(dL);
      uint32_t o[4], q8[2];
      o[0] = pack2(phi(dL[0], r0, l0e), phi(dL[1], r0, l0e)); o[1] = pack2(phi(dL[2], r1, l1e), phi(dL[3], r1, l1e));
      o[2] = pack2(dL[4] * r0, dL[5] * r0); o[3] = pack2(dL[6] * r1, dL[7] * r1);
      q8[0] = pack2(phi(dL[8], r0, l0e), phi(dL[9], r0, l0e)); q8[1] = pack2(phi(dL[10], r1, l1e), phi(dL[11], r1, l1e));
      uint32_t lo = ((j & 1) ? 0 : 8 * 2048) + warp * 256 + lane * 4;
      pinr(o);
      asm volatile("" : "+r"(q8[0]), "+r"(q8[1]), "+r"(lo)::"memory");
      fin1(5, 0);
      sts32(sb + PK_T + lo, o[0]); sts32(sb + PK_T + lo + 128, o[1]);
      sts32(sb + V_T + lo, o[2]); sts32(sb + V_T + lo + 128, o[3]);
      sts64(sb + Q8 + tid * 8, q8[0], q8[1]);
    }
    uint32_t hs = sb + HB + wg * HHALF + (tid & 127) * 16 + 4096;
    uint32_t hp[4];
    float iq0, iq1;
    auto epiF = [&](float (&d)[32], const int pc) {
      asm volatile("" : "+f"(d[4 * pc]), "+f"(d[4 * pc + 1]), "+f"(d[4 * pc + 2]), "+f"(d[4 * pc + 3]), "+f"(d[4 * pc + 16]), "+f"(d[4 * pc + 17]),
                   "+f"(d[4 * pc + 18]), "+f"(d[4 * pc + 19])::"memory");
      const float g0 = d[4 * pc], g1 = d[4 * pc + 1], g2 = d[4 * pc + 2], g3 = d[4 * pc + 3];
      hp[2 * (pc & 1)] = pack2(g0 * d[4 * pc + 16] * rcp(fmaf(ex2(-g0 * l0e), iq0, iq0)), g1 * d[4 * pc + 17] * rcp(fmaf(ex2(-g1 * l0e), iq0, iq0)));
      hp[2 * (pc & 1) + 1] = pack2(g2 * d[4 * pc + 18] * rcp(fmaf(ex2(-g2 * l1e), iq1, iq1)), g3 * d[4 * pc + 19] * rcp(fmaf(ex2(-g3 * l1e), iq1, iq1)));
      asm volatile("" : "+r"(hp[2 * (pc & 1)]), "+r"(hp[2 * (pc & 1) + 1])::"memory");
    };
    auto sth = [&](const int k) { sts128(hs + k * 2048, hp[0], hp[1], hp[2], hp[3]); };
    {
      mm(dB, 1, 0);
      iq0 = rcp(r0 * r0); iq1 = rcp(r1 * r1);
      fence_async_smem();
      __syncwarp();
      if (l0) mbar_arrive(sb + B_KVT);
      fin1(0, 1);
      mm(dB, 1, 1); epiF(dA, 0); epiF(dA, 1); fin1(1, 1); sth(0);
      mm(dB, 1, 2); epiF(dA, 2); epiF(dA, 3);
      mbar_spin(sb + B_KVT, 0);
      fin1(2, 1); sth(1);
      float dK[20];
      const uint64_t ka = mkdesc(sb + V_T - 2048 + wg * 3 * 2048, 128, 2048, 0), kb = mkdesc(sb + PK_T + wg * 4 * 2048, 128, 2048, 0);
      wg_fence();
#pragma unroll
      for (int ks = 0; ks < 8; ks++) wgmma_ss40tt(dK, ka + ks * 16, kb + ks * 16, ks != 0);
      wg_commit();
      mm0(dB, 1, 3);
      float4* dst = g_kvp + (j * 16 + r) * 1280 + warp * 160 + lane;
      asm volatile("" : "+l"(dst)::"memory");
      const bool used = warp != 3 && warp != 4;
      fin1(3, 1);
      pin(dK);
      if (used) {
#pragma unroll
        for (int t = 0; t < 2; t++) __stcg(dst + t * 32, make_float4(dK[4 * t], dK[4 * t + 1], dK[4 * t + 2], dK[4 * t + 3]));
      }
      mm(dB, 1, 4); fin1(4, 1);
      if (used) {
#pragma unroll
        for (int t = 2; t < 5; t++) __stcg(dst + t * 32, make_float4(dK[4 * t], dK[4 * t + 1], dK[4 * t + 2], dK[4 * t + 3]));
      }
      __syncwarp();
      if (l0) mbar_arrive(sb + B_KVD);
    }
#pragma unroll 1
    for (int it = 0; it < 8; it++) {
      mm(dB, 1, 5); fin1(5, 1);
      mm(dA, 1, 0);
      hs = __shfl_sync(0xffffffffu, hs + 8192, lane);
      fin1(0, 0);
#pragma unroll
      for (int s = 1; s < 5; s++) { mm(dA, 1, s); epiF(dB, s - 1); fin1(s, 0); if (!(s & 1)) sth(s / 2 - 3); }
      mm(dA, 1, 5); fin1(5, 0);
      mm(dB, 1, 0); fin1(0, 1);
#pragma unroll
      for (int s = 1; s < 5; s++) { mm(dB, 1, s); epiF(dA, s - 1); fin1(s, 1); if (!(s & 1)) sth(s / 2 - 1); }
    }
    mm(dB, 1, 5); fin1(5, 1);
    const uint32_t hl = sb + HB + wg * HHALF + (tid & 127) * 16;
    auto reload = [&](auto k0, auto k1) {
      static_for<decltype(k0)::value, decltype(k1)::value>([&](auto k) { lds128_inplace<decltype(k)::value * 2048>(a[decltype(k)::value], hl); });
    };
    mm(dA, 0, 0);
    mbar_spin(sb + B_MRDY, 0);
    fin1(0, 0);
    auto keep = [&](const int k) {
#pragma unroll
      for (int i = 0; i < 4; i++) mov_inplace(a[k][i], hp[i], hl);
    };
    mm(dA, 0, 1); epiF(dB, 0); fin1(1, 0);
    reload(IC<2>(), IC<5>());
    mm(dA, 0, 2); epiF(dB, 1); keep(0); fin1(2, 0);
    reload(IC<5>(), IC<9>());
    mm(dA, 0, 3); epiF(dB, 2); fin1(3, 0);
    reload(IC<9>(), IC<12>());
    mm(dA, 0, 4); epiF(dB, 3); keep(1); fin1(4, 0);
    reload(IC<12>(), IC<16>());
    mm(dA, 0, 5); fin1(5, 0);
    reload(IC<16>(), IC<19>());
    const uint32_t ot = sb + HB + wg * HHALF;
    uint64_t do_a = mkdesc(ot + 4 * 256, 128, 1280, 0), do_b = p.dob;
    auto mmO = [&](float (&d)[32]) {
      wg_fence();
#pragma unroll
      for (int ks = 0; ks < 5; ks++) wgmma_ss64(d, do_a, ks == 0 ? p.backa : 16, do_b, ks == 0 ? p.backb : 128);
      wg_commit();
    };
    uint32_t tag;
    {
      mm(dB, 0, 0);
      asm volatile("" : "+f"(l0e), "+f"(l1e));
      r0 = l0e * (1.f / LOG2E); r1 = l1e * (1.f / LOG2E);
      fin1(0, 1);
      reload(IC<19>(), IC<23>());
      uint32_t pq[5][4];
      auto phiq = [&](const int t0, const int t1) {
#pragma unroll
        for (int t = t0; t < t1; t++) {
          asm volatile("" : "+f"(dA[4 * t]), "+f"(dA[4 * t + 1]), "+f"(dA[4 * t + 2]), "+f"(dA[4 * t + 3])::"memory");
          pq[t >> 1][2 * (t & 1)] = pack2(phi(dA[4 * t], r0, l0e), phi(dA[4 * t + 1], r0, l0e));
          pq[t >> 1][2 * (t & 1) + 1] = pack2(phi(dA[4 * t + 2], r1, l1e), phi(dA[4 * t + 3], r1, l1e));
          asm volatile("" : "+r"(pq[t >> 1][2 * (t & 1)]), "+r"(pq[t >> 1][2 * (t & 1) + 1])::"memory");
        }
      };
      tag = lds32(sb + TAGW);
      mm(dB, 0, 1); phiq(0, 2); fin1(1, 1);
      reload(IC<23>(), IC<26>());
      mm(dB, 0, 2); phiq(2, 4); fin1(2, 1);
      reload(IC<26>(), IC<30>());
      mm(dB, 0, 3); phiq(4, 6); fin1(3, 1);
      reload(IC<30>(), IC<34>());
      lds64(pq[4][0], pq[4][1], sb + Q8 + tid * 8);
      mm(dB, 0, 4);
      phiq(6, 8);
      pq[4][2] = pq[4][3] = 0;
      pinr(pq[4]);
      fin1(4, 1);
      reload(IC<34>(), IC<36>());
      float den[8];
      wg_fence();
#pragma unroll
      for (int ks = 0; ks < 5; ks++) wgmma_rs16(den, pq[ks], p.dz + ks * 16, ks != 0);
      wg_commit();
#pragma unroll
      for (int ks = 30; ks < 34; ks++) wgmma_rs64(dB, a[ks], DESC(0, ks), 1);
      wg_commit();
      const int u = __shfl_sync(0xffffffffu, 2 * (lane & 3) + 8 * (j & 1), lane);
      const uint32_t oa = __shfl_sync(0xffffffffu, ot + ((warp & 3) * 2 + ((lane >> 3) & 1)) * 1280 + (lane >> 4) * 128 + (lane & 7) * 16, lane);
      fin(6, 0, 4);
      pin(den);
      uint32_t iv[8];
#pragma unroll
      for (int i = 0; i < 8; i++) { const float t = rcp(den[i] + 1e-6f); iv[i] = pack2(t, t); }
#pragma unroll
      for (int tt = 0; tt < 9; tt++) {
        const int lo = tt == 0 ? 0 : tt >= 7 ? 3 : (tt - 1) >> 1, hi = tt == 8 ? 0 : (tt == 0 || tt == 7) ? lo : lo + 1;
        const bool up = tt == 8 ? (j & 1) : 8 * tt + u >= 18 * hi;
        const int il = (lo >> 1) * 4 + (lo & 1), ih = (hi >> 1) * 4 + (hi & 1);
        pq[tt >> 1][2 * (tt & 1)] = bmul2(pq[tt >> 1][2 * (tt & 1)], up ? iv[ih] : iv[il]);
        pq[tt >> 1][2 * (tt & 1) + 1] = bmul2(pq[tt >> 1][2 * (tt & 1) + 1], up ? iv[ih + 2] : iv[il + 2]);
      }
#pragma unroll
      for (int ks = 0; ks < 5; ks++) stsm4(oa + ks * 256, pq[ks][0], pq[ks][1], pq[ks][2], pq[ks][3]);
      wg_fence();
#pragma unroll
      for (int ks = 0; ks < 5; ks++) wgmma_rs64(dB, pq[ks], do_b, ks == 0 ? p.backb : 128, 1);
      wg_commit();
#pragma unroll
      for (int ks = 34; ks < 36; ks++) wgmma_rs64(dB, a[ks], DESC(0, ks), 1);
      wg_commit();
      fence_async_smem();
      fin(0, 0, 6);
    }
    uint4* const pbase = g_part + (size_t)r * 9 * 8 * 1024 + warp * 128 + lane;
    uint32_t v[16], o[4][4];
    uint4* dst;
    auto cvtP = [&](float (&d)[32], const int h) {
#pragma unroll
      for (int z = 0; z < 2; z++) {
        const int i = 2 * h + z;
        pin8(d, 8 * i);
        o[i][0] = ((__float_as_uint(d[8 * i + 1]) + 0x10000u) & 0xfffe0000u) | pack2(d[8 * i], __uint_as_float(tag)); o[i][1] = pack2(d[8 * i + 2], d[8 * i + 3]);
        o[i][2] = pack2(d[8 * i + 4], d[8 * i + 5]); o[i][3] = pack2(d[8 * i + 6], d[8 * i + 7]);
        pinr(o[i]);
      }
    };
    auto padr = [&](const int c, const int src) {
      uint4* q = pbase + (c * 8 + src) * 1024;
      asm volatile("" : "+l"(q)::"memory");
      return q;
    };
    auto stP = [&](uint4* dst, const int h) {
      st_b128(dst + 64 * h, o[2 * h][0], o[2 * h][1], o[2 * h][2], o[2 * h][3]);
      st_b128(dst + 64 * h + 32, o[2 * h + 1][0], o[2 * h + 1][1], o[2 * h + 1][2], o[2 * h + 1][3]);
    };
    auto ldp = [&](uint32_t (&v)[16], const uint4* src) {
#pragma unroll
      for (int i = 0; i < 4; i++) ld_b128(v[4 * i], v[4 * i + 1], v[4 * i + 2], v[4 * i + 3], src + i * 32);
    };
    auto chk = [&](uint32_t (&v)[16], const int c, const int src) {
      while (__builtin_expect(__any_sync(0xffffffffu, (((v[0] ^ tag) | (v[4] ^ tag) | (v[8] ^ tag) | (v[12] ^ tag)) & 0x10000u) != 0), 0)) ldp(v, padr(c, src));
    };
    auto unp = [&](float (&d)[32], uint32_t (&v)[16], const int i) {
      d[8 * i] = blo(v[4 * i]); d[8 * i + 1] = __uint_as_float(v[4 * i] & 0xfffe0000u); d[8 * i + 2] = blo(v[4 * i + 1]); d[8 * i + 3] = bhi(v[4 * i + 1]);
      d[8 * i + 4] = blo(v[4 * i + 2]); d[8 * i + 5] = bhi(v[4 * i + 2]); d[8 * i + 6] = blo(v[4 * i + 3]); d[8 * i + 7] = bhi(v[4 * i + 3]);
      pin8(d, 8 * i);
    };
    auto stepP = [&](float (&x)[32], float (&y)[32], const uint32_t ph, const int n) {
      const int cl = (j + n + 1) & 7;
      mm(x, 0, 1);
      cvtP(y, 0); cvtP(y, 1);
      fin(2, ph, 0);
      stP(dst, 0);
      mm(x, 0, 2);
      const uint4* src = padr(cl, (j + 3) & 7);
      fin(3, ph, 1);
      if (n > 2) ldp(v, src);
      stP(dst, 1);
      mm(x, 0, 3); fin(4, ph, 2);
      mm(x, 0, 4); fin(5, ph, 3);
      mm(x, 0, 5);
      fin(6, ph ^ 1, 4);
      chk(v, cl, (j + 3) & 7);
      mmO(x);
      unp(y, v, 0); unp(y, v, 1); unp(y, v, 2); unp(y, v, 3);
      fin(0, ph ^ 1, 5);
      mm(y, 0, 0, 1);
      dst = padr((j + n) & 7, j);
      fin(1, ph ^ 1, 6);
    };
    mm(dA, 0, 0);
    dst = padr(8, j);
#pragma unroll
    for (int i = 0; i < 16; i++) v[i] = (i & 3) ? 0u : tag;
    fin(1, 0, 5);
#pragma unroll 1
    for (int n = 1;; n += 2) {
      stepP(dA, dB, 0, n);
      if (n == 7) break;
      stepP(dB, dA, 1, n + 1);
    }
    {
      uint32_t w[16], xv[16];
      float f[32] = {};
      auto addv = [&](uint32_t (&v)[16], const int i) {
        f[8 * i] += blo(v[4 * i]); f[8 * i + 1] += __uint_as_float(v[4 * i] & 0xfffe0000u); f[8 * i + 2] += blo(v[4 * i + 1]); f[8 * i + 3] += bhi(v[4 * i + 1]);
        f[8 * i + 4] += blo(v[4 * i + 2]); f[8 * i + 5] += bhi(v[4 * i + 2]); f[8 * i + 6] += blo(v[4 * i + 3]); f[8 * i + 7] += bhi(v[4 * i + 3]);
        pin8(f, 8 * i);
      };
      rd[0] += p.backa + 64;
      cvtP(dA, 0); cvtP(dA, 1);
      stP(dst, 0); stP(dst, 1);
      mm(dB, 0, 1);
      const uint4* src = padr(j, (j + 2) & 7);
      fin(2, 1, -1);
      ldp(v, src);
      mm(dB, 0, 2);
      const uint32_t ln = ((uint32_t)(size_t)dst >> 4) & 31;
      const uint32_t xa = sb + XT + (warp * 16 + (ln & 15)) * 128 + (((ln >> 4) ^ (ln & 7)) << 4);
      const uint32_t ps = sb + HB + wg * HHALF + STG + (warp & 3) * 2048;
      mbar_spin(sb + B_X, 1);
      fin(3, 1, -1);
#pragma unroll
      for (int i = 0; i < 4; i++) ldsm4(xv[4 * i], xv[4 * i + 1], xv[4 * i + 2], xv[4 * i + 3], xa ^ (i * 32));
      mm(dB, 0, 3);
      src = padr(j, (j + 1) & 7);
      fin(4, 1, -1);
      mm(dB, 0, 4);
#pragma unroll
      for (int i = 0; i < 16; i++) { f[2 * i] = blo(xv[i]); f[2 * i + 1] = bhi(xv[i]); }
      fin(5, 1, -1);
      chk(v, j, (j + 2) & 7);
      ldp(w, src);
      mm(dB, 0, 5);
      addv(v, 0); addv(v, 1);
      fin(6, 0, -1);
      mmO(dB);
      addv(v, 2); addv(v, 3);
      const uint32_t sa = ps + (ln & 15) * 128 + (((ln >> 4) ^ (ln & 7)) << 4);
      const uint32_t la = ps + (ln >> 3) * 128 + (((ln & 7) ^ (ln >> 3)) << 4);
      uint4* op = reinterpret_cast<uint4*>(p.out) + ((r * 128 + warp * 16 + (ln >> 3)) * 72 + 8 * j + (ln & 7));
      mbar_spin(sb + B_FULL + 48, 0);
      chk(w, j, (j + 1) & 7);
      addv(w, 0); addv(w, 1); addv(w, 2); addv(w, 3);
      wg_wait<0>();
      pin(dB);
#pragma unroll
      for (int t = 0; t < 8; t += 2)
        stsm4(sa ^ (t * 16),
              pack2(f[4 * t] + dB[4 * t], f[4 * t + 1] + dB[4 * t + 1]), pack2(f[4 * t + 2] + dB[4 * t + 2], f[4 * t + 3] + dB[4 * t + 3]),
              pack2(f[4 * t + 4] + dB[4 * t + 4], f[4 * t + 5] + dB[4 * t + 5]), pack2(f[4 * t + 6] + dB[4 * t + 6], f[4 * t + 7] + dB[4 * t + 7]));
      __syncwarp();
      uint4 q[4];
#pragma unroll
      for (int i = 0; i < 4; i++) lds128(q[i].x, q[i].y, q[i].z, q[i].w, (la ^ ((i & 1) * 64)) + i * 512);
      if (ln == 0) mbar_arrive(sb + B_DONE);
#pragma unroll
      for (int i = 0; i < 4; i++) op[i * 4 * 72] = q[i];
    }
  }
}

typedef CUresult (*EncodeFn)(CUtensorMap*, CUtensorMapDataType, cuuint32_t, void*, const cuuint64_t*, const cuuint64_t*, const cuuint32_t*,
                             const cuuint32_t*, CUtensorMapInterleave, CUtensorMapSwizzle, CUtensorMapL2promotion, CUtensorMapFloatOOBfill);

CUtensorMap make_map(EncodeFn enc, const void* ptr, int rows, int cols, int brow, int bcol, CUtensorMapSwizzle sw) {
  CUtensorMap m;
  cuuint64_t gd[2] = {(cuuint64_t)cols, (cuuint64_t)rows};
  cuuint64_t gs[1] = {(cuuint64_t)cols * 2};
  cuuint32_t bd[2] = {(cuuint32_t)bcol, (cuuint32_t)brow};
  cuuint32_t es[2] = {1, 1};
  enc(&m, CU_TENSOR_MAP_DATA_TYPE_BFLOAT16, 2, const_cast<void*>(ptr), gd, gs, bd, es, CU_TENSOR_MAP_INTERLEAVE_NONE, sw,
      CU_TENSOR_MAP_L2_PROMOTION_L2_128B, CU_TENSOR_MAP_FLOAT_OOB_FILL_NONE);
  return m;
}

}

extern "C" void kernel_launch(void* const* d_in, const int* in_sizes, int n_in, void* d_out, int out_size) {
  (void)in_sizes; (void)n_in; (void)out_size;
  static EncodeFn enc = nullptr;
  static void* m_ptr = nullptr;
  if (!enc) {
    cudaGetSymbolAddress(&m_ptr, g_M);
    cudaDriverEntryPointQueryResult qr;
    cudaGetDriverEntryPoint("cuTensorMapEncodeTiled", (void**)&enc, cudaEnableDefault, &qr);
    cudaFuncSetAttribute(fused_block_kernel, cudaFuncAttributeMaxDynamicSharedMemorySize, SMEM_BYTES);
  }
  Params p;
  p.x = (const __nv_bfloat16*)d_in[0];
  p.wqkv = (const __nv_bfloat16*)d_in[1];
  p.wo = (const __nv_bfloat16*)d_in[2];
  p.out = (__nv_bfloat16*)d_out;
  for (int i = 0; i < 2; i++) { p.d0[i] = ring_desc(i, 35); p.back[i] = (int64_t)(ring_desc(i, 0) - ring_desc(i, 35)); }
  p.dl = mkdesc(1024 + L24_T, 128, 576 * 16, 0);
  p.dz = mkdesc(1024 + ZM, 128, 1280, 0);
  p.dob = mkdesc(1024 + WO_SLOT + 4 * 2048, 16, 1024, 1);
  p.backa = -4 * 16;
  p.backb = -4 * 128;
  const CUtensorMap m_qkv = make_map(enc, p.wqkv, D_, 3 * D_, 96, 64, CU_TENSOR_MAP_SWIZZLE_128B);
  const CUtensorMap m_w1 = make_map(enc, d_in[4], D_, F_, 96, 32, CU_TENSOR_MAP_SWIZZLE_64B);
  const CUtensorMap m_w3 = make_map(enc, d_in[5], D_, F_, 96, 32, CU_TENSOR_MAP_SWIZZLE_64B);
  const CUtensorMap m_w2 = make_map(enc, d_in[6], F_, D_, 96, 64, CU_TENSOR_MAP_SWIZZLE_128B);
  const CUtensorMap m_M = make_map(enc, m_ptr, 8 * 80, D_, 80, 64, CU_TENSOR_MAP_SWIZZLE_128B);
  const CUtensorMap m_x = make_map(enc, p.x, 2048, D_, 128, 64, CU_TENSOR_MAP_SWIZZLE_128B);
  fused_block_kernel<<<132, NTHREADS, SMEM_BYTES>>>(p, m_x, m_qkv, m_w1, m_w3, m_w2, m_M);
}
```
